```python
import torch

def _softmax(x, axis=-1):
    return torch.softmax(x, dim=axis)
def _gelu(x):
    return torch.nn.functional.gelu(x, approximate="tanh")
def _silu(x):
    return torch.nn.functional.silu(x)
def _sigmoid(x):
    return torch.sigmoid(x)
def _layernorm(x, axis=-1, eps=1e-5):
    m = x.mean(dim=axis, keepdim=True)
    v = x.var(dim=axis, keepdim=True, unbiased=False)
    return (x - m) / torch.sqrt(v + eps)
def _scatter_add(tgt, idx, src, axis=0):
    return tgt.clone().index_add_(axis, idx, src)
def _segment_sum(src, seg, n):
    out = torch.zeros((n,) + src.shape[1:], dtype=src.dtype)
    return out.index_add_(0, seg, src)
def _pad(x, pw):
    flat = tuple(v for pair in reversed(pw) for v in pair)
    return torch.nn.functional.pad(x, flat)

kernel_name = 'recurrent_scan__compressed_kv_cla__moe_arch_mod__prompt'

def setup_inputs():

    _w = (lambda a: (lambda t: t.to(torch.bfloat16) if t.is_floating_point() else t)(torch.as_tensor(a)))
    def _A_setup():
        B, H, Sq, Sk, D, M = 1, 32, 2048, 2048, 128, 1024
        Dc = 4 * D
        return {
            "x": _w((lambda *s: torch.randn(*s, dtype=torch.bfloat16) * 0.05)(B, Sq, M)),
            "c_kv": _w((lambda *s: torch.randn(*s, dtype=torch.bfloat16) * 0.2)(B, Sk, Dc)),
            "w_q": _w((lambda *s: torch.randn(*s, dtype=torch.bfloat16) * 3.2)(M, H, D) * (M ** -0.5)),
            "w_uk": _w((lambda *s: torch.randn(*s, dtype=torch.bfloat16) * 3.2)(Dc, H, D) * (Dc ** -0.5)),
            "w_uv": _w((lambda *s: torch.randn(*s, dtype=torch.bfloat16) * 0.2)(Dc, H, D) * (Dc ** -0.5)),
            "w_o": _w((lambda *s: torch.randn(*s, dtype=torch.bfloat16) * 0.2)(H, D, M) * ((H * D) ** -0.5)),
        }
    _A_in = _A_setup()

    def _B_setup():
        B, S, D, F, C = 1, 2048, 1024, 3584, 2
        return {
            "x": _w((lambda *s: torch.randn(*s, dtype=torch.bfloat16) * 0.05)(B, S, D)),
            "w_r": _w((lambda *s: torch.randn(*s, dtype=torch.bfloat16) * 0.2)(D)),
            "w_gate": _w((lambda *s: torch.randn(*s, dtype=torch.bfloat16) * 0.1)(D, F)),
            "w_up": _w((lambda *s: torch.randn(*s, dtype=torch.bfloat16) * 0.1)(D, F)),
            "w_down": _w((lambda *s: torch.randn(*s, dtype=torch.bfloat16) * 0.1)(F, D)),
        }
    _B_in = _B_setup()

    return {
        "A_x": _A_in["x"],
        "A_c_kv": _A_in["c_kv"],
        "A_w_q": _A_in["w_q"],
        "A_w_uk": _A_in["w_uk"],
        "A_w_uv": _A_in["w_uv"],
        "A_w_o": _A_in["w_o"],
        "B_x": _B_in["x"],
        "B_w_r": _B_in["w_r"],
        "B_w_gate": _B_in["w_gate"],
        "B_w_up": _B_in["w_up"],
        "B_w_down": _B_in["w_down"],
    }

def reference(A_x, A_c_kv, A_w_q, A_w_uk, A_w_uv, A_w_o, B_x, B_w_r, B_w_gate, B_w_up, B_w_down):
    def _A_ref(x, c_kv, w_q, w_uk, w_uv, w_o):
        B, Sq, M = x.shape[0], x.shape[1], x.shape[2]
        Sk = c_kv.shape[1]
        H, D = w_q.shape[1], w_q.shape[2]
        q = torch.einsum("bqm,mhd->bhqd", x, w_q)
        k = torch.einsum("bkc,chd->bhkd", c_kv, w_uk)
        v = torch.einsum("bkc,chd->bhkd", c_kv, w_uv)
        scores = torch.einsum("bhqd,bhkd->bhqk", q, k) * (D ** -0.5)
        off = Sk - Sq
        qi = torch.arange(Sq)[:, None]
        kj = torch.arange(Sk)[None, :]
        cmask = kj <= (qi + off)
        scores = torch.where(cmask[None, None], scores, -1e9)
        p = _softmax(scores, axis=-1)
        ctx = torch.einsum("bhqk,bhkd->bhqd", p, v)
        return torch.einsum("bhqd,hdm->bqm", ctx, w_o)

    def _B_ref(x, w_r, w_gate, w_up, w_down):
        B, S, D = x.shape
        C = 2
        r = x @ w_r
        idx = torch.argsort(-r, axis=-1)[:, :C]
        idx_e = (lambda x, n, axis: torch.repeat_interleave(x, n, dim=axis))(idx.reshape(B, C, 1), D, axis=2)
        x_sel = (lambda x, i, axis: torch.take_along_dim(x, i, dim=axis))(x, idx_e, axis=1)
        g = _silu(x_sel @ w_gate)
        u = x_sel @ w_up
        y = (g * u) @ w_down
        r_sel = _sigmoid((lambda x, i, axis: torch.take_along_dim(x, i, dim=axis))(r, idx, axis=1))
        y = y * r_sel.reshape(B, C, 1)
        b_off = (torch.arange(B) * S).reshape(B, 1)
        flat_idx = (idx + b_off).reshape(B * C)
        zero = (x * 0.0).reshape(B * S, D)
        upd = _scatter_add(zero, flat_idx, y.reshape(B * C, D), axis=0)
        return x + upd.reshape(B, S, D)

    x = A_x
    xn = _layernorm(x, axis=-1)
    s = _A_ref(xn, A_c_kv, A_w_q, A_w_uk, A_w_uv, A_w_o)
    g = _silu(_B_ref(xn, B_w_r, B_w_gate, B_w_up, B_w_down))
    return x + s * g
```

```cpp
#include <cuda_runtime.h>
#include <cuda_bf16.h>
#include <cuda.h>
#include <stdint.h>

namespace {

constexpr int SEQ = 2048, DM = 1024, NH = 32, DC = 512, FF = 3584;
constexpr int PAGE = 16384;
constexpr int NRING = 12;
constexpr int NCTA = 132, NMAIN = 128;
constexpr uint32_t SM_REGION = NRING * PAGE;
constexpr uint32_t SM_BAR = (NRING + 2) * PAGE;
constexpr uint32_t BAR_FULL = SM_BAR, BAR_EMPTY = SM_BAR + 64;
constexpr uint32_t BAR_DEP = SM_BAR + 128;
constexpr uint32_t BAR_G = SM_BAR + 184;
constexpr uint32_t BAR_DONE = SM_BAR + 200;
constexpr uint32_t BAR_EMPTYL = SM_BAR + 216;
constexpr int NBAR = 35;
constexpr uint32_t SM_PROF = SM_BAR + 320;
constexpr int SMEM_BYTES = SM_PROF + 512;
constexpr uint32_t SPIN_LIMIT = 1u << 16;
constexpr uint32_t POLL_MASK = 7;

struct SyncBlock {
    unsigned done;       unsigned pad0[31];
    unsigned ln;         unsigned pad1[31];
    unsigned router;     unsigned pad4[31];
    unsigned ffn_ticket; unsigned pad2[31];
    unsigned ffn_done;   unsigned pad3[31];
    unsigned kv[NH * 8];
    unsigned kvfree[16 * 8];
    unsigned ctx[32 * NH];
};

__device__ __align__(1024) uint8_t g_xn[8 * 16 * 4 * 8192];
__device__ __align__(1024) uint8_t g_kv[16 * 16 * 65536];
__device__ __align__(1024) uint8_t g_ctx[16 * 64 * 16384];
__device__ __align__(16) uint4 g_routed[2 * 128];
__device__ int g_sel[2];
__device__ __align__(16) float g_r[SEQ];
__device__ __align__(16) float g_ypart[4 * 2 * DM];
__device__ SyncBlock g_sync;

__device__ __forceinline__ uint32_t smem_u32(const void* p) { return (uint32_t)__cvta_generic_to_shared(p); }

__device__ __forceinline__ void mbar_init(uint32_t bar, uint32_t count) {
    asm volatile("mbarrier.init.shared::cta.b64 [%0], %1;" ::"r"(bar), "r"(count) : "memory");
}
#define MBAR_WAIT_ASM(HINT, LIMIT)                                                                  \
    asm volatile("{\n.reg .pred p;\n.reg .u32 n;\nmov.u32 n, 0;\n"                                  \
                 "WAIT_LOOP:\n"                                                                     \
                 "mbarrier.try_wait.parity.shared::cta.b64 p, [%0], %1" HINT ";\n"                  \
                 "@p bra WAIT_DONE;\n"                                                              \
                 "add.u32 n, n, 1;\n"                                                               \
                 "setp.lt.u32 p, n, " LIMIT ";\n"                                                   \
                 "@p bra WAIT_LOOP;\n"                                                              \
                 "WAIT_DONE:\n}\n" ::"r"(bar), "r"(parity) : "memory")
__device__ __forceinline__ void mbar_wait(uint32_t bar, uint32_t parity) { MBAR_WAIT_ASM("", "131072"); }
__device__ __forceinline__ void mbar_sleep(uint32_t bar, uint32_t parity) { MBAR_WAIT_ASM(", 2000", "8192"); }
__device__ __forceinline__ bool mbar_try(uint32_t bar, uint32_t parity) {
    uint32_t ok;
    asm volatile("{\n.reg .pred p;\nmbarrier.try_wait.parity.shared::cta.b64 p, [%1], %2;\nselp.u32 %0, 1, 0, p;\n}\n"
                 : "=r"(ok) : "r"(bar), "r"(parity) : "memory");
    return ok;
}
__device__ __forceinline__ bool mbar_test(uint32_t bar, uint32_t parity) {
    uint32_t ok;
    asm volatile("{\n.reg .pred p;\nmbarrier.test_wait.parity.shared::cta.b64 p, [%1], %2;\nselp.u32 %0, 1, 0, p;\n}\n"
                 : "=r"(ok) : "r"(bar), "r"(parity) : "memory");
    return ok;
}
__device__ __forceinline__ bool elect_one() {
    uint32_t ok;
    asm volatile("{\n.reg .pred p;\nelect.sync _|p, 0xffffffff;\nselp.u32 %0, 1, 0, p;\n}\n" : "=r"(ok));
    return ok;
}
__device__ __forceinline__ void mbar_arrive(uint32_t bar) {
    asm volatile("mbarrier.arrive.shared::cta.b64 _, [%0];" ::"r"(bar) : "memory");
}
__device__ __forceinline__ void mbar_expect_tx(uint32_t bar, uint32_t bytes) {
    asm volatile("mbarrier.arrive.expect_tx.shared::cta.b64 _, [%0], %1;" ::"r"(bar), "r"(bytes) : "memory");
}
__device__ __forceinline__ void mbar_arrive_cluster(uint32_t cluster_addr) {
    asm volatile("mbarrier.arrive.shared::cluster.b64 _, [%0];" ::"r"(cluster_addr) : "memory");
}
__device__ __forceinline__ uint32_t mapa(uint32_t addr, uint32_t rank) {
    uint32_t r;
    asm("mapa.shared::cluster.u32 %0, %1, %2;" : "=r"(r) : "r"(addr), "r"(rank));
    return r;
}
__device__ __forceinline__ void tma_3d(uint32_t dst, const CUtensorMap* m, int c0, int c1, int c2, uint32_t bar) {
    asm volatile("cp.async.bulk.tensor.3d.shared::cluster.global.mbarrier::complete_tx::bytes [%0], [%1, {%3, %4, %5}], [%2];"
                 ::"r"(dst), "l"(m), "r"(bar), "r"(c0), "r"(c1), "r"(c2) : "memory");
}
__device__ __forceinline__ void tma_3d_hint(uint32_t dst, const CUtensorMap* m, int c0, int c1, int c2, uint32_t bar, uint64_t pol) {
    asm volatile("cp.async.bulk.tensor.3d.shared::cluster.global.mbarrier::complete_tx::bytes.L2::cache_hint [%0], [%1, {%3, %4, %5}], [%2], %6;"
                 ::"r"(dst), "l"(m), "r"(bar), "r"(c0), "r"(c1), "r"(c2), "l"(pol) : "memory");
}
__device__ __forceinline__ void tma_3d_mc(uint32_t dst, const CUtensorMap* m, int c0, int c1, int c2, uint32_t bar) {
    asm volatile("cp.async.bulk.tensor.3d.shared::cluster.global.mbarrier::complete_tx::bytes.multicast::cluster [%0], [%1, {%3, %4, %5}], [%2], %6;"
                 ::"r"(dst), "l"(m), "r"(bar), "r"(c0), "r"(c1), "r"(c2), "h"((uint16_t)3) : "memory");
}
__device__ __forceinline__ void tma_5d_mc(uint32_t dst, const CUtensorMap* m, int c0, int c4, uint32_t bar) {
    asm volatile("cp.async.bulk.tensor.5d.shared::cluster.global.mbarrier::complete_tx::bytes.multicast::cluster [%0], [%1, {%3, 0, 0, 0, %4}], [%2], %5;"
                 ::"r"(dst), "l"(m), "r"(bar), "r"(c0), "r"(c4), "h"((uint16_t)3) : "memory");
}
__device__ __forceinline__ void bulk_load(uint32_t dst, const void* src, uint32_t bytes, uint32_t bar) {
    asm volatile("cp.async.bulk.shared::cluster.global.mbarrier::complete_tx::bytes [%0], [%1], %2, [%3];"
                 ::"r"(dst), "l"(src), "r"(bytes), "r"(bar) : "memory");
}
__device__ __forceinline__ void cp_async16(uint32_t dst, const void* src) {
    asm volatile("cp.async.cg.shared.global [%0], [%1], 16;" ::"r"(dst), "l"(src) : "memory");
}
__device__ __forceinline__ void bulk_load_mc(uint32_t dst, const void* src, uint32_t bytes, uint32_t bar) {
    asm volatile("cp.async.bulk.shared::cluster.global.mbarrier::complete_tx::bytes.multicast::cluster [%0], [%1], %2, [%3], %4;"
                 ::"r"(dst), "l"(src), "r"(bytes), "r"(bar), "h"((uint16_t)3) : "memory");
}
__device__ __forceinline__ void tma_store_2d(const CUtensorMap* m, int c0, int c1, uint32_t src) {
    asm volatile("cp.async.bulk.tensor.2d.global.shared::cta.bulk_group [%0, {%2, %3}], [%1];"
                 ::"l"(m), "r"(src), "r"(c0), "r"(c1) : "memory");
}
__device__ __forceinline__ void bulk_commit() { asm volatile("cp.async.bulk.commit_group;" ::: "memory"); }
__device__ __forceinline__ void bulk_wait_read() { asm volatile("cp.async.bulk.wait_group.read 0;" ::: "memory"); }
__device__ __forceinline__ void fence_async_smem() { asm volatile("fence.proxy.async.shared::cta;" ::: "memory"); }
__device__ __forceinline__ void prefetch_map(const CUtensorMap* m) {
    asm volatile("prefetch.tensormap [%0];" ::"l"(m) : "memory");
}
__device__ __forceinline__ void red_release(unsigned* p) {
    asm volatile("red.release.gpu.global.add.u32 [%0], 1;" ::"l"(p) : "memory");
}
__device__ __forceinline__ unsigned ld_relaxed(const unsigned* p) {
    unsigned v;
    asm volatile("ld.relaxed.gpu.global.u32 %0, [%1];" : "=r"(v) : "l"(p) : "memory");
    return v;
}
__device__ __forceinline__ void wait_counter(const unsigned* p, unsigned target, unsigned ns = 100) {
    for (uint32_t n = 0; (int)(ld_relaxed(p) - target) < 0 && n < SPIN_LIMIT; n++) __nanosleep(ns);
    asm volatile("fence.acquire.gpu;" ::: "memory");
    asm volatile("fence.proxy.async.global;" ::: "memory");
}
__device__ __forceinline__ void bar_sync(int id, int n) { asm volatile("bar.sync %0, %1;" ::"r"(id), "r"(n) : "memory"); }
__device__ __forceinline__ void bar_arrive(int id, int n) { asm volatile("bar.arrive %0, %1;" ::"r"(id), "r"(n) : "memory"); }
__device__ __forceinline__ void cluster_sync() {
    asm volatile("barrier.cluster.arrive.relaxed.aligned;\nbarrier.cluster.wait.aligned;" ::: "memory");
}
__device__ __forceinline__ void wg_fence() { asm volatile("wgmma.fence.sync.aligned;" ::: "memory"); }
__device__ __forceinline__ void wg_commit() { asm volatile("wgmma.commit_group.sync.aligned;" ::: "memory"); }
template <int N> __device__ __forceinline__ void wg_wait() { asm volatile("wgmma.wait_group.sync.aligned %0;" ::"n"(N) : "memory"); }
template <int N> __device__ __forceinline__ void reg_fence(float (&a)[N]) {
#pragma unroll
    for (int i = 0; i < N; i++) asm volatile("" : "+f"(a[i])::"memory");
}
template <int N> __device__ __forceinline__ void reg_fence(uint32_t (&a)[N]) {
#pragma unroll
    for (int i = 0; i < N; i++) asm volatile("" : "+r"(a[i])::"memory");
}
__device__ __forceinline__ uint32_t pack_bf16(float lo, float hi) {
    uint32_t r;
    asm("cvt.rn.bf16x2.f32 %0, %1, %2;" : "=r"(r) : "f"(hi), "f"(lo));
    return r;
}
__device__ __forceinline__ float bf_lo(uint32_t v) { return __uint_as_float(v << 16); }
__device__ __forceinline__ float bf_hi(uint32_t v) { return __uint_as_float(v & 0xffff0000u); }
__device__ __forceinline__ float bf_round(float v) { return __bfloat162float(__float2bfloat16_rn(v)); }
__device__ __forceinline__ float ex2(float v) {
    float r;
    asm("ex2.approx.ftz.f32 %0, %1;" : "=f"(r) : "f"(v));
    return r;
}
__device__ __forceinline__ float sqrt_approx(float v) {
    float r;
    asm("sqrt.approx.ftz.f32 %0, %1;" : "=f"(r) : "f"(v));
    return r;
}
__device__ __forceinline__ float rcp_approx(float v) {
    float r;
    asm("rcp.approx.ftz.f32 %0, %1;" : "=f"(r) : "f"(v));
    return r;
}
__device__ __forceinline__ float silu_f(float v) { return v * rcp_approx(1.0f + ex2(v * -1.4426950408889634f)); }
__device__ __forceinline__ void stmatrix_x4(uint32_t addr, uint32_t r0, uint32_t r1, uint32_t r2, uint32_t r3) {
    asm volatile("stmatrix.sync.aligned.m8n8.x4.shared.b16 [%0], {%1, %2, %3, %4};"
                 ::"r"(addr), "r"(r0), "r"(r1), "r"(r2), "r"(r3) : "memory");
}
__device__ __forceinline__ void sts128(uint32_t addr, uint32_t r0, uint32_t r1, uint32_t r2, uint32_t r3) {
    asm volatile("st.shared.v4.b32 [%0], {%1, %2, %3, %4};" ::"r"(addr), "r"(r0), "r"(r1), "r"(r2), "r"(r3) : "memory");
}
__device__ __forceinline__ void lds128(uint32_t addr, uint32_t& r0, uint32_t& r1, uint32_t& r2, uint32_t& r3) {
    asm volatile("ld.shared.v4.b32 {%0, %1, %2, %3}, [%4];" : "=r"(r0), "=r"(r1), "=r"(r2), "=r"(r3) : "r"(addr) : "memory");
}
__device__ __forceinline__ void ldmatrix_x4(uint32_t addr, uint32_t& r0, uint32_t& r1, uint32_t& r2, uint32_t& r3) {
    asm volatile("ldmatrix.sync.aligned.m8n8.x4.shared.b16 {%0, %1, %2, %3}, [%4];"
                 : "=r"(r0), "=r"(r1), "=r"(r2), "=r"(r3) : "r"(addr) : "memory");
}
__device__ __forceinline__ uint32_t bf2_mul(uint32_t a, uint32_t b) {
    uint32_t r;
    asm("mul.rn.bf16x2 %0, %1, %2;" : "=r"(r) : "r"(a), "r"(b));
    return r;
}
__device__ __forceinline__ uint32_t bf2_add(uint32_t a, uint32_t b) {
    uint32_t r;
    asm("add.rn.bf16x2 %0, %1, %2;" : "=r"(r) : "r"(a), "r"(b));
    return r;
}
__device__ __forceinline__ uint64_t policy_evict_first() {
    uint64_t p;
    asm("createpolicy.fractional.L2::evict_first.b64 %0, 1.0;" : "=l"(p));
    return p;
}

__device__ __forceinline__ uint64_t make_desc(uint32_t addr, uint32_t lbo_bytes) {
    return (uint64_t)((addr & 0x3FFFF) >> 4) | ((uint64_t)(lbo_bytes >> 4) << 16) | ((uint64_t)(1024 >> 4) << 32) | (1ull << 62);
}

__device__ __forceinline__ void wgmma_n256_ss(float (&d)[128], uint64_t da, uint64_t db, int acc) {
    asm volatile(
        "{\n.reg .pred p;\nsetp.ne.b32 p, %130, 0;\n"
        "wgmma.mma_async.sync.aligned.m64n256k16.f32.bf16.bf16 {"
        "%0, %1, %2, %3, %4, %5, %6, %7, %8, %9, %10, %11, %12, %13, %14, %15, "
        "%16, %17, %18, %19, %20, %21, %22, %23, %24, %25, %26, %27, %28, %29, %30, %31, "
        "%32, %33, %34, %35, %36, %37, %38, %39, %40, %41, %42, %43, %44, %45, %46, %47, "
        "%48, %49, %50, %51, %52, %53, %54, %55, %56, %57, %58, %59, %60, %61, %62, %63, "
        "%64, %65, %66, %67, %68, %69, %70, %71, %72, %73, %74, %75, %76, %77, %78, %79, "
        "%80, %81, %82, %83, %84, %85, %86, %87, %88, %89, %90, %91, %92, %93, %94, %95, "
        "%96, %97, %98, %99, %100, %101, %102, %103, %104, %105, %106, %107, %108, %109, %110, %111, "
        "%112, %113, %114, %115, %116, %117, %118, %119, %120, %121, %122, %123, %124, %125, %126, %127"
        "}, %128, %129, p, 1, 1, 1, 0;\n}\n"
        :
        "+f"(d[0]), "+f"(d[1]), "+f"(d[2]), "+f"(d[3]), "+f"(d[4]), "+f"(d[5]), "+f"(d[6]), "+f"(d[7]),
        "+f"(d[8]), "+f"(d[9]), "+f"(d[10]), "+f"(d[11]), "+f"(d[12]), "+f"(d[13]), "+f"(d[14]), "+f"(d[15]),
        "+f"(d[16]), "+f"(d[17]), "+f"(d[18]), "+f"(d[19]), "+f"(d[20]), "+f"(d[21]), "+f"(d[22]), "+f"(d[23]),
        "+f"(d[24]), "+f"(d[25]), "+f"(d[26]), "+f"(d[27]), "+f"(d[28]), "+f"(d[29]), "+f"(d[30]), "+f"(d[31]),
        "+f"(d[32]), "+f"(d[33]), "+f"(d[34]), "+f"(d[35]), "+f"(d[36]), "+f"(d[37]), "+f"(d[38]), "+f"(d[39]),
        "+f"(d[40]), "+f"(d[41]), "+f"(d[42]), "+f"(d[43]), "+f"(d[44]), "+f"(d[45]), "+f"(d[46]), "+f"(d[47]),
        "+f"(d[48]), "+f"(d[49]), "+f"(d[50]), "+f"(d[51]), "+f"(d[52]), "+f"(d[53]), "+f"(d[54]), "+f"(d[55]),
        "+f"(d[56]), "+f"(d[57]), "+f"(d[58]), "+f"(d[59]), "+f"(d[60]), "+f"(d[61]), "+f"(d[62]), "+f"(d[63]),
        "+f"(d[64]), "+f"(d[65]), "+f"(d[66]), "+f"(d[67]), "+f"(d[68]), "+f"(d[69]), "+f"(d[70]), "+f"(d[71]),
        "+f"(d[72]), "+f"(d[73]), "+f"(d[74]), "+f"(d[75]), "+f"(d[76]), "+f"(d[77]), "+f"(d[78]), "+f"(d[79]),
        "+f"(d[80]), "+f"(d[81]), "+f"(d[82]), "+f"(d[83]), "+f"(d[84]), "+f"(d[85]), "+f"(d[86]), "+f"(d[87]),
        "+f"(d[88]), "+f"(d[89]), "+f"(d[90]), "+f"(d[91]), "+f"(d[92]), "+f"(d[93]), "+f"(d[94]), "+f"(d[95]),
        "+f"(d[96]), "+f"(d[97]), "+f"(d[98]), "+f"(d[99]), "+f"(d[100]), "+f"(d[101]), "+f"(d[102]), "+f"(d[103]),
        "+f"(d[104]), "+f"(d[105]), "+f"(d[106]), "+f"(d[107]), "+f"(d[108]), "+f"(d[109]), "+f"(d[110]), "+f"(d[111]),
        "+f"(d[112]), "+f"(d[113]), "+f"(d[114]), "+f"(d[115]), "+f"(d[116]), "+f"(d[117]), "+f"(d[118]), "+f"(d[119]),
        "+f"(d[120]), "+f"(d[121]), "+f"(d[122]), "+f"(d[123]), "+f"(d[124]), "+f"(d[125]), "+f"(d[126]), "+f"(d[127])
        : "l"(da), "l"(db), "r"(acc));
}

template <int TB>
__device__ __forceinline__ void wgmma_n128_rs(float (&d)[64], uint32_t a0, uint32_t a1, uint32_t a2, uint32_t a3, uint64_t db, int acc) {
    asm volatile(
        "{\n.reg .pred p;\nsetp.ne.b32 p, %69, 0;\n"
        "wgmma.mma_async.sync.aligned.m64n128k16.f32.bf16.bf16 {"
        "%0, %1, %2, %3, %4, %5, %6, %7, %8, %9, %10, %11, %12, %13, %14, %15, "
        "%16, %17, %18, %19, %20, %21, %22, %23, %24, %25, %26, %27, %28, %29, %30, %31, "
        "%32, %33, %34, %35, %36, %37, %38, %39, %40, %41, %42, %43, %44, %45, %46, %47, "
        "%48, %49, %50, %51, %52, %53, %54, %55, %56, %57, %58, %59, %60, %61, %62, %63"
        "}, {%64, %65, %66, %67}, %68, p, 1, 1, %70;\n}\n"
        :
        "+f"(d[0]), "+f"(d[1]), "+f"(d[2]), "+f"(d[3]), "+f"(d[4]), "+f"(d[5]), "+f"(d[6]), "+f"(d[7]),
        "+f"(d[8]), "+f"(d[9]), "+f"(d[10]), "+f"(d[11]), "+f"(d[12]), "+f"(d[13]), "+f"(d[14]), "+f"(d[15]),
        "+f"(d[16]), "+f"(d[17]), "+f"(d[18]), "+f"(d[19]), "+f"(d[20]), "+f"(d[21]), "+f"(d[22]), "+f"(d[23]),
        "+f"(d[24]), "+f"(d[25]), "+f"(d[26]), "+f"(d[27]), "+f"(d[28]), "+f"(d[29]), "+f"(d[30]), "+f"(d[31]),
        "+f"(d[32]), "+f"(d[33]), "+f"(d[34]), "+f"(d[35]), "+f"(d[36]), "+f"(d[37]), "+f"(d[38]), "+f"(d[39]),
        "+f"(d[40]), "+f"(d[41]), "+f"(d[42]), "+f"(d[43]), "+f"(d[44]), "+f"(d[45]), "+f"(d[46]), "+f"(d[47]),
        "+f"(d[48]), "+f"(d[49]), "+f"(d[50]), "+f"(d[51]), "+f"(d[52]), "+f"(d[53]), "+f"(d[54]), "+f"(d[55]),
        "+f"(d[56]), "+f"(d[57]), "+f"(d[58]), "+f"(d[59]), "+f"(d[60]), "+f"(d[61]), "+f"(d[62]), "+f"(d[63])
        : "r"(a0), "r"(a1), "r"(a2), "r"(a3), "l"(db), "r"(acc), "n"(TB));
}

__device__ __forceinline__ void wgmma_n128_ss(float* d, uint64_t da, uint64_t db, int acc) {
    asm volatile(
        "{\n.reg .pred p;\nsetp.ne.b32 p, %66, 0;\n"
        "wgmma.mma_async.sync.aligned.m64n128k16.f32.bf16.bf16 {"
        "%0, %1, %2, %3, %4, %5, %6, %7, %8, %9, %10, %11, %12, %13, %14, %15, "
        "%16, %17, %18, %19, %20, %21, %22, %23, %24, %25, %26, %27, %28, %29, %30, %31, "
        "%32, %33, %34, %35, %36, %37, %38, %39, %40, %41, %42, %43, %44, %45, %46, %47, "
        "%48, %49, %50, %51, %52, %53, %54, %55, %56, %57, %58, %59, %60, %61, %62, %63"
        "}, %64, %65, p, 1, 1, 0, 1;\n}\n"
        :
        "+f"(d[0]), "+f"(d[1]), "+f"(d[2]), "+f"(d[3]), "+f"(d[4]), "+f"(d[5]), "+f"(d[6]), "+f"(d[7]),
        "+f"(d[8]), "+f"(d[9]), "+f"(d[10]), "+f"(d[11]), "+f"(d[12]), "+f"(d[13]), "+f"(d[14]), "+f"(d[15]),
        "+f"(d[16]), "+f"(d[17]), "+f"(d[18]), "+f"(d[19]), "+f"(d[20]), "+f"(d[21]), "+f"(d[22]), "+f"(d[23]),
        "+f"(d[24]), "+f"(d[25]), "+f"(d[26]), "+f"(d[27]), "+f"(d[28]), "+f"(d[29]), "+f"(d[30]), "+f"(d[31]),
        "+f"(d[32]), "+f"(d[33]), "+f"(d[34]), "+f"(d[35]), "+f"(d[36]), "+f"(d[37]), "+f"(d[38]), "+f"(d[39]),
        "+f"(d[40]), "+f"(d[41]), "+f"(d[42]), "+f"(d[43]), "+f"(d[44]), "+f"(d[45]), "+f"(d[46]), "+f"(d[47]),
        "+f"(d[48]), "+f"(d[49]), "+f"(d[50]), "+f"(d[51]), "+f"(d[52]), "+f"(d[53]), "+f"(d[54]), "+f"(d[55]),
        "+f"(d[56]), "+f"(d[57]), "+f"(d[58]), "+f"(d[59]), "+f"(d[60]), "+f"(d[61]), "+f"(d[62]), "+f"(d[63])
        : "l"(da), "l"(db), "r"(acc));
}

__device__ __forceinline__ void wgmma_n8_ta(float* d, uint64_t da, uint64_t db) {
    asm volatile("wgmma.mma_async.sync.aligned.m64n8k16.f32.bf16.bf16 {%0, %1, %2, %3}, %4, %5, 1, 1, 1, 1, 0;\n"
                 : "+f"(d[0]), "+f"(d[1]), "+f"(d[2]), "+f"(d[3]) : "l"(da), "l"(db));
}

__device__ __forceinline__ void wgmma_n8(float* d, uint64_t da, uint64_t db) {
    asm volatile("wgmma.mma_async.sync.aligned.m64n8k16.f32.bf16.bf16 {%0, %1, %2, %3}, %4, %5, 1, 1, 1, 0, 0;\n"
                 : "+f"(d[0]), "+f"(d[1]), "+f"(d[2]), "+f"(d[3]) : "l"(da), "l"(db));
}

#define PROF(slot, role)
#undef PROF_GT
#define PROF_GT(slot)

struct Params {
    const __nv_bfloat16* x;
    const __nv_bfloat16* w_r;
    const uint8_t *c_kv, *w_uk, *w_uv, *w_o;
};
__device__ __forceinline__ void lsu_prefetch(const void* p) { asm volatile("prefetch.global.L2 [%0];" ::"l"(p) : "memory"); }

template <typename T>
__device__ __forceinline__ T* ptr_off(T* base, uint32_t off) {
    uint32_t lo, hi;
    asm("mov.b64 {%0, %1}, %2;" : "=r"(lo), "=r"(hi) : "l"(base));
    asm("add.cc.u32 %0, %0, %2;\naddc.u32 %1, %1, 0;" : "+r"(lo), "+r"(hi) : "r"(off));
    T* r;
    asm("mov.b64 %0, {%1, %2};" : "=l"(r) : "r"(lo), "r"(hi));
    return r;
}
__device__ __forceinline__ int attn_rowblock(int pair, int seg) {
    int j = pair & 3, hl = pair >> 2;
    return (((hl & 1) | (j == 0)) ^ seg) ? j : 7 - j;
}
__device__ __forceinline__ int outproj_head(int i, int ib) {
    if (i < 16) return i;
    return 16 + 2 * (i & 7) + ((ib < 4) ^ ((i >> 3) & 1));
}

__device__ __forceinline__ void pin_value(uint32_t& v) { asm volatile("" : "+r"(v)); }
__device__ __forceinline__ void pin_value(int& v) { asm volatile("" : "+r"(v)); }
__device__ __forceinline__ void pin_value(const uint8_t*& v) { asm volatile("" : "+l"(v)); }

__device__ __forceinline__ void producer(const Params& P, uint32_t sb, int pair, int c,
                                         const CUtensorMap* m_ckv, const CUtensorMap* m_wuk, const CUtensorMap* m_wuv,
                                         const CUtensorMap* m_wq, const CUtensorMap* m_wo, const CUtensorMap* m_x,
                                         const CUtensorMap* m_out) {
    const int hl = pair >> 2;
    const int ibA = attn_rowblock(pair, 0), nA = 2 * ibA + 2;
    const int ib = (pair >> 1) & 7, mi = 2 * ib + c, nb = (pair >> 4) * 4 + (pair & 1) * 2;
    const bool leader = elect_one();
    uint32_t g = 4, tail = 0;
    if (leader) prefetch_map(m_wq);
    auto wait_released = [&](uint32_t need) {
#pragma unroll 1
        for (; tail <= need; tail++) mbar_wait(sb + BAR_EMPTY + (tail & 7) * 8, (tail >> 3) & 1);
    };
    auto wait_released_here = [&](uint32_t need) {
#pragma unroll 1
        for (; tail < need; tail++) mbar_wait(sb + BAR_EMPTY + (tail & 7) * 8, (tail >> 3) & 1);
        if (tail == need) mbar_wait(sb + BAR_EMPTYL + (need & 7) * 8, (need >> 3) & 1);
    };
    auto wait_released_peer = [&](uint32_t need) {
        if (tail == need) {
            uint32_t eb = sb + BAR_EMPTY + (need & 7) * 8, ep = (need >> 3) & 1;
            tail++;
            mbar_wait(eb, ep);
        }
    };
    auto full_bar = [&]() { return sb + BAR_FULL + (g & 7) * 8; };
    auto pin = [](auto&... v) { (pin_value(v), ...); };
#pragma unroll 1
    for (int rnd = 0; rnd < 2; rnd++) {
#pragma unroll 1
        for (int i = rnd ? 0 : 4; i < 16; i++) {
            const bool fresh = (i >> 2) != 2;
            int kb = (i ^ (i >> 1 & 4)) & 7, h2 = ((pair & 15) + rnd * 16) * 2 + c, krow = kb * 64, tok = (pair >> 4) * 512 + (i & 8) * 32 + c * 128;
            uint32_t pg = sb + (i & 3) * (3 * PAGE), pb = pg + (1 + c) * PAGE, bar = full_bar();
            pin(kb, h2, krow, tok, pg, pb, bar);
            const uint32_t need = g - 4 - (i < 2);
            wait_released_here(need);
            if (leader) {
                mbar_expect_tx(bar, fresh ? 3 * PAGE : 2 * PAGE);
                if (fresh) {
                    tma_3d(pg, m_wuk, 0, krow, h2, bar);
                    tma_3d(pg + 8192, m_wuv, 0, krow, h2, bar);
                }
            }
            wait_released_peer(need);
            if (leader) {
                tma_3d_mc(pb, m_ckv, 0, tok, kb, bar);
                if (rnd == 1 && i == 3) asm volatile("red.relaxed.gpu.global.add.u32 [%0], 1;" ::"l"(ptr_off(g_sync.kvfree, hl * 32)) : "memory");
            }
            g++;
        }
        mbar_sleep(sb + BAR_DEP, 0);
        const uint8_t* xa = ptr_off(g_xn, ibA * (16 * 32768) + c * PAGE);
        const uint8_t* xb = ptr_off(g_xn, (7 - ibA) * (16 * 32768) + (1 - c) * PAGE);
#pragma unroll 1
        for (int kb = 0; kb < DM / 64; kb++) {
            uint32_t pg = sb + (kb & 3) * (3 * PAGE), pw = pg + 2 * PAGE + c * 8192, bar = full_bar(), p2 = pg + PAGE;
            int krow = kb * 64;
            pin(pg, pw, p2, bar, krow);
            wait_released_here(g - 4);
            if (leader) {
                mbar_expect_tx(bar, 3 * PAGE);
                bulk_load(pg, xa, PAGE, bar);
            }
            wait_released_peer(g - 4);
            if (leader) {
                tma_3d_mc(pw, m_wq, 0, krow, (rnd * 16 + hl) * 2 + c, bar);
                bulk_load(p2, xb, PAGE, bar);
            }
            g++;
            xa += 32768;
            xb += 32768;
        }
        mbar_sleep(sb + BAR_DEP + 8 + rnd * 16, 0);
        if (rnd == 1 && leader) prefetch_map(m_wo);
        uint32_t pg = sb + c * PAGE;
#pragma unroll 1
        for (int j = 0; j < 36; j++) {
            const bool isk = j == 0 || ((j & 1) && j != 35);
            const int t = isk ? (j + 1) >> 1 : (j - 1) >> 1;
            const uint8_t* src = ptr_off(g_kv, (hl * 16 + (t >= nA ? t - nA : t)) * 65536 + (isk ? 0 : 32768) + c * PAGE);
            uint32_t bar = full_bar(), need = g - 6 + (j < 2) + (j < 5);
            pin(src, bar, need);
            wait_released(need);
            if (leader) {
                mbar_expect_tx(bar, 2 * PAGE);
                bulk_load_mc(pg, src, PAGE, bar);
            }
            g++;
            if (rnd == 0 && j >= 22 && j < 30) {
                const int cta = pair * 2 + c, i = j - 22;
                const uint32_t l = (threadIdx.x & 31) * 128;
                lsu_prefetch(ptr_off(i & 1 ? P.w_uv : P.w_uk, cta * 32768 + (i >> 1) * 8192 + 4096 + l));
            }
            if (rnd == 1 && j >= 32) {
                const int cta = pair * 2 + c, i = j - 32;
                const uint32_t l = (threadIdx.x & 31) * 128;
                lsu_prefetch(ptr_off(P.w_o, (i * 128 + cta) * 4096 + l));
            }
            pg = pg >= sb + SM_REGION - 2 * PAGE ? pg - (SM_REGION - 2 * PAGE) : pg + 2 * PAGE;
        }
    }
    uint32_t pg = sb;
#pragma unroll 1
    for (int i = 0; i < 64; i++) {
        if (i == 32 && leader) { prefetch_map(m_x); prefetch_map(m_out); }
        if ((i & 15) == 0 && i != 16) mbar_sleep(sb + BAR_DEP + 32 + (i >> 1) - (i ? 8 : 0), 0);
        const int kb = outproj_head(i >> 1, ib) * 2 + (i & 1);
        const uint8_t* src = ptr_off(g_ctx, (mi * 64 + kb) * PAGE);
        uint32_t bar = full_bar(), pw = pg + PAGE + c * 8192;
        int krow = kb * 2;
        pin(src, bar, pw, krow);
        wait_released_here(g - 6);
        if (leader) {
            mbar_expect_tx(bar, 2 * PAGE);
            bulk_load(pg, src, PAGE, bar);
        }
        wait_released_peer(g - 6);
        if (leader) tma_5d_mc(pw, m_wo, (nb + c) * 64, krow, bar);
        g++;
        pg = pg == sb + SM_REGION - 2 * PAGE ? sb : pg + 2 * PAGE;
    }
    const uint32_t bar = full_bar();
    wait_released(g - 6);
    if (leader) {
        mbar_expect_tx(bar, 2 * PAGE);
        tma_3d(pg, m_x, 0, mi * 128, nb, bar);
        tma_3d(pg + PAGE, m_x, 0, mi * 128 + 64, nb, bar);
    }
}

__device__ __forceinline__ uint32_t xn_block(int row64, int kb) {
    return (((row64 >> 2) * 16 + kb) * 4 + ((row64 & 1) * 2 + (((row64 >> 1) & 1) ^ 1))) * 8192;
}
__device__ __forceinline__ uint32_t image_offset(int row, int ch) {
    return xn_block(row >> 6, ch >> 3) + (row & 63) * 128 + (((ch & 7) ^ (row & 7)) << 4);
}
__device__ __forceinline__ uint32_t bf2_sub(uint32_t a, uint32_t b) {
    uint32_t r;
    asm("sub.rn.bf16x2 %0, %1, %2;" : "=r"(r) : "r"(a), "r"(b));
    return r;
}
__device__ __forceinline__ uint32_t bf2_fma(uint32_t a, uint32_t b, uint32_t c) {
    uint32_t r;
    asm("fma.rn.bf16x2 %0, %1, %2, %3;" : "=r"(r) : "r"(a), "r"(b), "r"(c));
    return r;
}
template <int N0, int N>
__device__ __forceinline__ void ln_sums(const uint32_t (&u)[N], float& sum, float& sq) {
    float s0 = 0.f, s1 = 0.f, q0 = 0.f, q1 = 0.f;
#pragma unroll
    for (int k = N0; k < N0 + 16; k++) {
        const float a = bf_lo(u[k]), b = bf_hi(u[k]);
        s0 += a; s1 += b;
        q0 = fmaf(a, a, q0); q1 = fmaf(b, b, q1);
    }
    sum = s0 + s1;
    sq = q0 + q1;
}
__device__ __forceinline__ void ln_finish(float sum, float sq, uint32_t& mean2, uint32_t& rhi2, uint32_t& rlo2) {
    const float ms = sum * (1.0f / DM);
    const float var = fmaxf(fmaf(-ms, ms, sq * (1.0f / DM)), 0.f);
    const float rden = rcp_approx(bf_round(sqrt_approx(bf_round(bf_round(var) + 1e-5f))));
    const float rhi = bf_round(rden);
    mean2 = pack_bf16(ms, ms);
    rhi2 = pack_bf16(rhi, rhi);
    rlo2 = pack_bf16(rden - rhi, rden - rhi);
}
template <int N0, int N>
__device__ __forceinline__ void ln_apply(const uint32_t (&u)[N], uint32_t mean2, uint32_t rhi2, uint32_t rlo2, uint8_t* dst) {
#pragma unroll
    for (int i = 0; i < 4; i++) {
        uint32_t o[4];
#pragma unroll
        for (int k = 0; k < 4; k++) {
            const uint32_t d = bf2_sub(u[N0 + 4 * i + k], mean2);
            o[k] = bf2_fma(d, rhi2, bf2_mul(d, rlo2));
        }
        __stcg(reinterpret_cast<uint4*>(dst + i * 131072), make_uint4(o[0], o[1], o[2], o[3]));
    }
}
__device__ __forceinline__ int query_rowblock(int pair, int c, int w, int seg) {
    const int qA = (w ? 0 : 2) + c;
    return 4 * attn_rowblock(pair, seg) + (seg ? 3 - qA : qA);
}

__device__ __forceinline__ void fetch_helper(const uint8_t* c_kv, uint32_t sb, int w, int lane, int pair, int c) {
    const uint32_t page = sb + SM_REGION + w * PAGE + lane * 16;
    mbar_sleep(sb + BAR_FULL + 5 * 8, 0);
    lsu_prefetch(ptr_off(c_kv, (pair >> 4) * 524288 + 262144 + ((pair & 15) * 4 + c * 2 + w) * 4096 + lane * 128));
    const unsigned e1 = __ldcg(&g_sync.done) / NCTA + 1;
#pragma unroll 1
    for (int e = 1; e <= 7; e += 2) mbar_sleep(sb + BAR_DONE + 8, (e >> 1) & 1);
    const int rb = ((pair >> 1) & 7) * 4 + c * 2 + w, kb0 = (pair >> 4) * 4 + (pair & 1) * 2;
    const uint8_t* src = ptr_off(g_xn, xn_block(rb, kb0) + lane * 16);
#pragma unroll 1
    for (int i = 0; i < 32; i += 4) {
#pragma unroll
        for (int k = 0; k < 4; k++) cp_async16(page + (i + k) * 512, src + (i + k) * 512 + (i >> 4) * (32768 - 8192));
        __nanosleep(200);
    }
    wait_counter(&g_sync.ffn_done, e1);
    const int r = __ldcg(ptr_off(g_sel, (lane >> 4) * 4)) - rb * 64, ch = lane & 15;
    const uint4 t = __ldcg(ptr_off(g_routed, ((lane >> 4) * 128 + kb0 * 8 + ch) * 16));
    asm volatile("cp.async.wait_all;" ::: "memory");
    __syncwarp();
    if (r >= 0 && r < 64)
        sts128(sb + SM_REGION + w * PAGE + (ch >> 3) * 8192 + r * 128 + (((ch & 7) ^ (r & 7)) << 4), t.x, t.y, t.z, t.w);
    __syncwarp();
    if (lane == 0) mbar_arrive(sb + BAR_G + w * 8);
    PROF(20, 2);
}

__device__ __noinline__ void sync_helper(uint32_t sb, int lane, int pair, int c) {
    const unsigned e1 = __ldcg(&g_sync.done) / NCTA + 1;
    const int ib = (pair >> 1) & 7;
    int e = 0, b = 0;
#pragma unroll 1
    for (uint32_t n = 0; (e < 9 || b < 7) && n < SPIN_LIMIT; n++) {
        if (e < 9 && __all_sync(~0u, mbar_test(sb + BAR_DONE + (e & 1) * 8, (e >> 1) & 1))) {
            const int rnd = e > 4, ev = (e - 1) & 3;
            unsigned* flag = e == 0 ? &g_sync.ln
                           : ev < 2 ? ptr_off(g_sync.kv, (rnd * 16 + (pair & 15)) * 32)
                                    : ptr_off(g_sync.ctx, (query_rowblock(pair, c, lane & 1, ev & 1) * NH + rnd * 16 + (pair >> 2)) * 4);
            asm volatile("fence.proxy.async.global;\nfence.release.gpu;" ::: "memory");
            if (lane < ((e == 0 || ev < 2) ? 1 : 2)) asm volatile("red.relaxed.gpu.global.add.u32 [%0], 1;" ::"l"(flag) : "memory");
            PROF(10 + e, 2);
            e++;
        }
        if (b < 7 && e > 0 && (b < 4 || (n & POLL_MASK) == 0)) {
            const int i = b == 4 ? lane >> 1 : 8 * b - 24 + ((lane >> 1) & 7);
            const unsigned* cnt = b == 0 ? &g_sync.ln
                                : b == 2 ? ptr_off(g_sync.kvfree, (pair & 15) * 32)
                                : b < 4 ? ptr_off(g_sync.kv, ((b >> 1) * 16 + (pair >> 2)) * 32)
                                        : ptr_off(g_sync.ctx, ((4 * ib + 2 * c + (lane & 1)) * NH + outproj_head(i & 31, ib)) * 4);
            if (__all_sync(~0u, (int)(ld_relaxed(cnt) - e1 * (b == 0 ? NMAIN : b == 2 ? 8 : b < 4 ? 16 : 1)) >= 0)) {
                asm volatile("fence.acquire.gpu;\nfence.proxy.async.global;" ::: "memory");
                __syncwarp();
                if (lane == 0) mbar_arrive(sb + BAR_DEP + b * 8);
                PROF(1 + b, 2);
                b++;
            }
        }
        __nanosleep(150);
    }
}

__device__ __forceinline__ unsigned long long block_max_key(unsigned long long k, unsigned long long* red, int tid) {
#pragma unroll
    for (int o = 16; o; o >>= 1) {
        unsigned long long t = __shfl_xor_sync(~0u, k, o);
        k = t > k ? t : k;
    }
    bar_sync(1, 256);
    if ((tid & 31) == 0) red[tid >> 5] = k;
    bar_sync(1, 256);
    k = red[0];
#pragma unroll
    for (int i = 1; i < 8; i++) k = red[i] > k ? red[i] : k;
    return k;
}

constexpr int FS = FF / 4;
constexpr int FSTAGE = 32768, FNST = 6;
constexpr int FN0 = 32, FN1 = 2 * (DM / 16), FN2 = FS / 16;
constexpr uint32_t XB = FNST * FSTAGE, HB = XB + 16384, AUX = HB + 14336, PAUSE = AUX + 192;
constexpr int PAUSE_AT = 100;

__device__ __forceinline__ void ffn_producer(uint32_t sb, int s, unsigned e1, const CUtensorMap* m_gate, const CUtensorMap* m_up,
                                             const CUtensorMap* m_down) {
    const uint64_t pol = policy_evict_first();
    int slot = 0, ph = 1;
    wait_counter(&g_sync.ln, e1 * NMAIN);
#pragma unroll 1
    for (int st = -FN0; st < FN1 + FN2; st++) {
        mbar_sleep(sb + BAR_EMPTY + slot * 8, ph);
        const uint32_t bar = sb + BAR_FULL + slot * 8;
        if (st < 0) {
            mbar_expect_tx(bar, FSTAGE);
            bulk_load(sb + slot * FSTAGE, ptr_off(g_xn, (s * FN0 + FN0 + st) * FSTAGE), FSTAGE, bar);
        } else {
            if (st >= PAUSE_AT) {
                uint32_t p;
                for (uint32_t n = 0; n < 100; n++) {
                    asm volatile("ld.volatile.shared.u32 %0, [%1];" : "=r"(p) : "r"(sb + PAUSE) : "memory");
                    if (!p) break;
                    __nanosleep(200);
                }
            }
            const bool up = st < FN1;
            mbar_expect_tx(bar, up ? FS * 32 : DM * 32);
            tma_3d_hint(sb + slot * FSTAGE, up ? ((st & 1) ? m_up : m_gate) : m_down, 0,
                        up ? (st >> 1) * 16 : s * FS + (st - FN1) * 16, up ? s * (FS / 64) : 0, bar, pol);
        }
        if (++slot == FNST) { slot = 0; ph ^= 1; }
    }
}
__device__ __forceinline__ void ffn_pacer(uint32_t sb, unsigned e1) {
    wait_counter(&g_sync.kvfree[0], e1 * 8, 500);
    asm volatile("st.volatile.shared.u32 [%0], 1;" ::"r"(sb + PAUSE) : "memory");
    wait_counter(&g_sync.kv[16 * 8], e1 * 16, 500);
    asm volatile("st.volatile.shared.u32 [%0], 0;" ::"r"(sb + PAUSE) : "memory");
}

__device__ __forceinline__ void ffn_cta(uint8_t* smem, uint32_t sb, int s, unsigned epoch, const __nv_bfloat16* w_r) {
    const int tid = threadIdx.x, lane = tid & 31;
    const int warp = __shfl_sync(~0u, tid >> 5, 0), w = warp >> 2;
    unsigned long long* red = reinterpret_cast<unsigned long long*>(smem + AUX);
    unsigned* flag = reinterpret_cast<unsigned*>(smem + AUX + 128);
    const unsigned e1 = epoch + 1;
    for (int i = tid; i < (16384 + 14336) / 16; i += 256) reinterpret_cast<uint4*>(smem + XB)[i] = make_uint4(0, 0, 0, 0);
    int slot = 0, ph = 0, prev = 0;
    auto next_stage = [&](bool has_prev) {
        wg_commit();
        wg_wait<1>();
        if (has_prev && lane < 2) mbar_arrive(sb + BAR_EMPTY + prev * 8);
        prev = slot;
        if (++slot == FNST) { slot = 0; ph ^= 1; }
    };
    {
        bar_sync(1, 256);
        if (tid < 128) *reinterpret_cast<uint4*>(smem + XB + (tid >> 3) * 1024 + (tid & 7) * 16) = __ldg(reinterpret_cast<const uint4*>(w_r) + tid);
        fence_async_smem();
        bar_sync(1, 256);
#pragma unroll 1
        for (int blk = 0; blk < 2; blk++) {
            float ar[8];
#pragma unroll
            for (int i = 0; i < 8; i++) ar[i] = 0.f;
#pragma unroll 1
            for (int kb = 0; kb < 16; kb++) {
                const uint64_t db = make_desc(sb + XB + kb * 1024, 16);
                mbar_wait(sb + BAR_FULL + slot * 8, ph);
                const uint64_t da = make_desc(sb + slot * FSTAGE + w * 16384, 16);
                wg_fence();
#pragma unroll
                for (int q = 0; q < 4; q++) {
                    wgmma_n8(ar, da + 2 * q, db + 2 * q);
                    wgmma_n8(ar + 4, da + 512 + 2 * q, db + 2 * q);
                }
                next_stage(blk + kb > 0);
            }
            wg_wait<0>();
            reg_fence(ar);
            if ((lane & 3) == 0) {
#pragma unroll
                for (int i = 0; i < 4; i++)
                    __stcg(&g_r[(s * 2 + blk) * 256 + (w + 2 - (i & 2)) * 64 + (warp & 3) * 16 + (lane >> 2) + (i & 1) * 8], bf_round(ar[2 * i]));
            }
        }
        __threadfence();
        bar_sync(1, 256);
        if (tid == 0) {
            red_release(&g_sync.router);
            wait_counter(&g_sync.router, e1 * 4);
        }
        bar_sync(1, 256);
    }
    unsigned long long keys[8];
    unsigned long long best = 0;
#pragma unroll
    for (int i = 0; i < 8; i++) {
        int idx = tid + 256 * i;
        uint32_t b = __float_as_uint(__ldcg(&g_r[idx]) + 0.0f);
        b = (b & 0x80000000u) ? ~b : (b | 0x80000000u);
        keys[i] = ((unsigned long long)b << 32) | (unsigned)(SEQ - 1 - idx);
        best = keys[i] > best ? keys[i] : best;
    }
    const unsigned long long k0 = block_max_key(best, red, tid);
    best = 0;
#pragma unroll
    for (int i = 0; i < 8; i++) best = (keys[i] != k0 && keys[i] > best) ? keys[i] : best;
    const unsigned long long k1 = block_max_key(best, red, tid);
    const int row = SEQ - 1 - (int)((w ? k1 : k0) & 0xffffffffu);
    const int ch = tid & 127;
    const uint4 xrow = __ldcg(reinterpret_cast<const uint4*>(g_xn + image_offset(row, ch)));
    *reinterpret_cast<uint4*>(smem + XB + (ch >> 3) * 1024 + w * 128 + (((ch & 7) ^ w) << 4)) = xrow;
    fence_async_smem();
    bar_sync(1, 256);
    PROF(20, tid >> 7);
    {
        float ag[28], au[28];
#pragma unroll
        for (int i = 0; i < 28; i++) ag[i] = au[i] = 0.f;
#pragma unroll 1
        for (int ks = 0; ks < DM / 16; ks++) {
            const uint64_t db = make_desc(sb + XB + (ks >> 2) * 1024 + (ks & 3) * 32, 16);
            mbar_wait(sb + BAR_FULL + slot * 8, ph);
            uint64_t da = make_desc(sb + slot * FSTAGE + w * (7 * 2048), 16);
            wg_fence();
#pragma unroll
            for (int b = 0; b < 7; b++) wgmma_n8_ta(ag + 4 * b, da + b * 128, db);
            next_stage(true);
            mbar_wait(sb + BAR_FULL + slot * 8, ph);
            da = make_desc(sb + slot * FSTAGE + w * (7 * 2048), 16);
            wg_fence();
#pragma unroll
            for (int b = 0; b < 7; b++) wgmma_n8_ta(au + 4 * b, da + b * 128, db);
            next_stage(true);
        }
        wg_wait<0>();
        reg_fence(ag);
        reg_fence(au);
        if ((lane & 3) == 0) {
#pragma unroll
            for (int i = 0; i < 28; i++) {
                const int f = (warp & 3) * 16 + (lane >> 2) + (i & 2) * 4, tok = i & 1;
                const float h = bf_round(silu_f(bf_round(ag[i]))) * bf_round(au[i]);
                *reinterpret_cast<__nv_bfloat16*>(smem + HB + (w * 7 + (i >> 2)) * 1024 + tok * 128 + (((f >> 3) ^ tok) << 4) + (f & 7) * 2) =
                    __float2bfloat16_rn(h);
            }
        }
    }
    fence_async_smem();
    bar_sync(1, 256);
    PROF(21, tid >> 7);
    {
        float ay[32];
#pragma unroll
        for (int i = 0; i < 32; i++) ay[i] = 0.f;
#pragma unroll 1
        for (int ks = 0; ks < FN2; ks++) {
            const uint64_t db = make_desc(sb + HB + (ks >> 2) * 1024 + (ks & 3) * 32, 16);
            mbar_wait(sb + BAR_FULL + slot * 8, ph);
            const uint64_t da = make_desc(sb + slot * FSTAGE + w * (8 * 2048), 16);
            wg_fence();
#pragma unroll
            for (int b = 0; b < 8; b++) wgmma_n8_ta(ay + 4 * b, da + b * 128, db);
            next_stage(true);
        }
        wg_wait<0>();
        reg_fence(ay);
        if ((lane & 3) == 0) {
#pragma unroll
            for (int i = 0; i < 32; i++)
                g_ypart[(s * 2 + (i & 1)) * DM + (w * 8 + (i >> 2)) * 64 + (warp & 3) * 16 + (lane >> 2) + (i & 2) * 4] = ay[i];
        }
    }
    PROF(23, tid >> 7);
    __threadfence();
    bar_sync(1, 256);
    if (tid == 0) {
        *flag = atomicAdd(&g_sync.ffn_ticket, 1u) == epoch * 4 + 3;
        __threadfence();
    }
    bar_sync(1, 256);
    if (*flag) {
        const float sg = bf_round(__fdividef(1.0f, 1.0f + __expf(-__ldcg(&g_r[row]))));
        const uint32_t xu[4] = {xrow.x, xrow.y, xrow.z, xrow.w};
        uint32_t o[4];
#pragma unroll
        for (int k = 0; k < 4; k++) {
            float y0 = 0.f, y1 = 0.f;
#pragma unroll
            for (int q = 0; q < 4; q++) {
                const float2 y = __ldcg(reinterpret_cast<const float2*>(&g_ypart[(q * 2 + w) * DM + ch * 8 + 2 * k]));
                y0 += y.x; y1 += y.y;
            }
            o[k] = pack_bf16(bf_lo(xu[k]) + bf_round(bf_round(y0) * sg), bf_hi(xu[k]) + bf_round(bf_round(y1) * sg));
        }
        g_routed[w * 128 + ch] = make_uint4(o[0], o[1], o[2], o[3]);
        if (ch == 0) g_sel[w] = row;
        bar_sync(1, 256);
        if (tid == 0) red_release(&g_sync.ffn_done);
    }
}

__device__ __forceinline__ uint32_t slab_addr(uint32_t stg, int lane, int s) {
    const int row = ((lane >> 3) & 1) * 8 + (lane & 7);
    const int chunk = 2 * (s & 3) + (lane >> 4);
    return stg + row * 128 + (s >> 2) * 8192 + ((chunk ^ (lane & 7)) << 4);
}

constexpr float SM_SCALE = 0.08838834764831845f * 1.4426950408889634f;
constexpr float SUM_HI = 1048576.f, SUM_LO = 1.0f / 1048576.f;

template <int J0>
__device__ __forceinline__ void mask_half(float (&S)[64], float limf) {
    asm volatile("" : "+f"(limf));
#pragma unroll
    for (int i = 0; i < 32; i++) {
        const int j = i >> 2, key = 32 * (j >> 2) + 2 * (j & 3) + (i & 1) - 4 * (i & 2);
        float t;
        asm("add.sat.f32 %0, %1, %2;" : "=f"(t) : "f"((float)key), "f"(-limf));
        S[4 * J0 + i] = fmaf(t, -1e30f, S[4 * J0 + i]);
    }
}
__device__ __forceinline__ void issue_qk(float (&S)[64], const uint32_t (&Q)[32], uint64_t d0) {
#pragma unroll
    for (int s = 0; s < 8; s++)
        wgmma_n128_rs<1>(S, Q[4 * s], Q[4 * s + 1], Q[4 * s + 2], Q[4 * s + 3], d0 + s * 128, s > 0);
}
template <int S0, int S1>
__device__ __forceinline__ void issue_pv(float (&O)[64], const uint32_t (&Pm)[32], uint64_t d0, int acc) {
#pragma unroll
    for (int s = S0; s < S1; s++)
        wgmma_n128_rs<0>(O, Pm[4 * s], Pm[4 * s + 1], Pm[4 * s + 2], Pm[4 * s + 3], d0 + (s >> 2) * (PAGE >> 4) + (s & 3) * 2, s > 0 ? 1 : acc);
}
template <int J0, int J1>
__device__ __forceinline__ void exp_part(const float (&S)[64], uint32_t (&Pm)[32], float (&sum)[4]) {
#pragma unroll
    for (int i = 2 * J0; i < 2 * J1; i++) asm volatile("" : "+r"(Pm[i])::"memory");
#pragma unroll
    for (int j = J0; j < J1; j++) {
        const float e0 = ex2(S[4 * j]), e1 = ex2(S[4 * j + 1]), e2 = ex2(S[4 * j + 2]), e3 = ex2(S[4 * j + 3]);
        sum[0] += e0; sum[1] += e1; sum[2] += e2; sum[3] += e3;
        Pm[2 * j] = pack_bf16(e0, e1);
        Pm[2 * j + 1] = pack_bf16(e2, e3);
    }
}
__device__ __forceinline__ void shift_rows(float (&S)[64], float d0, float d1) {
#pragma unroll
    for (int j = 0; j < 16; j++) {
        S[4 * j] -= d0; S[4 * j + 1] -= d0; S[4 * j + 2] -= d1; S[4 * j + 3] -= d1;
    }
}
__device__ __forceinline__ void sched_fence(uint32_t& tick, bool on) {
    asm volatile("{\n.reg .pred p;\nsetp.ne.u32 p, %1, 0;\n@p mov.u32 %0, %%clock;\n}\n" : "+r"(tick) : "r"((uint32_t)on) : "memory");
}
constexpr int LAG = 4;
struct NoExtra { __device__ __forceinline__ void operator()(int) const {} };
template <int K0, int K1, int NP, int WAITAT, typename X = NoExtra>
__device__ __forceinline__ void exp_stages(const float (&S)[64], float (&e)[64], uint32_t (&Pm)[32], float (&sum)[4], uint32_t& tick, bool on,
                                           X extra = X()) {
#pragma unroll
    for (int k = K0; k < K1; k++) {
        if (k == WAITAT) wg_wait<1>();
        if (k < NP) {
            asm volatile("ex2.approx.ftz.f32 %0, %1;" : "=f"(e[2 * k]) : "f"(S[2 * k]));
            asm volatile("ex2.approx.ftz.f32 %0, %1;" : "=f"(e[2 * k + 1]) : "f"(S[2 * k + 1]));
        }
        if (k >= LAG) {
            const int i = 2 * (k - LAG);
            asm volatile("add.f32 %0, %0, %1;" : "+f"(sum[i & 3]) : "f"(e[i]));
            asm volatile("add.f32 %0, %0, %1;" : "+f"(sum[(i & 3) + 1]) : "f"(e[i + 1]));
            asm volatile("cvt.rn.bf16x2.f32 %0, %1, %2;" : "=r"(Pm[i / 2]) : "f"(e[i + 1]), "f"(e[i]));
        }
        extra(k);
        if (k >= LAG - 1 && k < NP - 1 && k != K1 - 1) sched_fence(tick, on);
    }
}
__device__ constexpr int chunk_src(int i) { return 4 * (4 * (i >> 3) + (i & 3)) + 2 * ((i >> 2) & 1); }
enum : uint32_t { CTL_START = 1, CTL_SWITCH = 2, CTL_DIRECT = 4, CTL_HALF = 8, CTL_MASKHI = 16, CTL_LOADQ = 32, CTL_PVHALF = 64, CTL_PVACC = 128 };
__device__ __forceinline__ float quad_sum(float v) {
    v += __shfl_xor_sync(~0u, v, 1);
    return v + __shfl_xor_sync(~0u, v, 2);
}

__device__ __forceinline__ void store_part(uint8_t* d0, int p, const uint32_t (&pk)[64]) {
    asm volatile("{\n.reg .b64 d1;\nxor.b64 d1, %0, 64;\n"
                 "TS: .branchtargets P0, P1, P2, P3, P4, P5, P6, P7;\n"
                 "brx.idx.uni %1, TS;\n"
                 "P0:\n st.global.cg.v4.u32 [%0 + 0], {%2, %3, %4, %5};\n st.global.cg.v4.u32 [d1 + 0], {%10, %11, %12, %13};\n bra.uni DONE;\n"
                 "P1:\n st.global.cg.v4.u32 [%0 + 1024], {%6, %7, %8, %9};\n st.global.cg.v4.u32 [d1 + 1024], {%14, %15, %16, %17};\n bra.uni DONE;\n"
                 "P2:\n st.global.cg.v4.u32 [%0 + 16384], {%18, %19, %20, %21};\n st.global.cg.v4.u32 [d1 + 16384], {%26, %27, %28, %29};\n bra.uni DONE;\n"
                 "P3:\n st.global.cg.v4.u32 [%0 + 17408], {%22, %23, %24, %25};\n st.global.cg.v4.u32 [d1 + 17408], {%30, %31, %32, %33};\n bra.uni DONE;\n"
                 "P4:\n st.global.cg.v4.u32 [%0 + 65536], {%34, %35, %36, %37};\n st.global.cg.v4.u32 [d1 + 65536], {%42, %43, %44, %45};\n bra.uni DONE;\n"
                 "P5:\n st.global.cg.v4.u32 [%0 + 66560], {%38, %39, %40, %41};\n st.global.cg.v4.u32 [d1 + 66560], {%46, %47, %48, %49};\n bra.uni DONE;\n"
                 "P6:\n st.global.cg.v4.u32 [%0 + 81920], {%50, %51, %52, %53};\n st.global.cg.v4.u32 [d1 + 81920], {%58, %59, %60, %61};\n bra.uni DONE;\n"
                 "P7:\n st.global.cg.v4.u32 [%0 + 82944], {%54, %55, %56, %57};\n st.global.cg.v4.u32 [d1 + 82944], {%62, %63, %64, %65};\n bra.uni DONE;\n"
                 "DONE:\n}\n"
                 ::"l"(d0), "r"(p), "r"(pk[0]), "r"(pk[1]), "r"(pk[2]), "r"(pk[3]), "r"(pk[4]), "r"(pk[5]), "r"(pk[6]), "r"(pk[7]), "r"(pk[8]), "r"(pk[9]), "r"(pk[10]), "r"(pk[11]), "r"(pk[12]), "r"(pk[13]), "r"(pk[14]), "r"(pk[15]), "r"(pk[16]), "r"(pk[17]), "r"(pk[18]), "r"(pk[19]), "r"(pk[20]), "r"(pk[21]), "r"(pk[22]), "r"(pk[23]), "r"(pk[24]), "r"(pk[25]), "r"(pk[26]), "r"(pk[27]), "r"(pk[28]), "r"(pk[29]), "r"(pk[30]), "r"(pk[31]), "r"(pk[32]), "r"(pk[33]), "r"(pk[34]), "r"(pk[35]), "r"(pk[36]), "r"(pk[37]), "r"(pk[38]), "r"(pk[39]), "r"(pk[40]), "r"(pk[41]), "r"(pk[42]), "r"(pk[43]), "r"(pk[44]), "r"(pk[45]), "r"(pk[46]), "r"(pk[47]), "r"(pk[48]), "r"(pk[49]), "r"(pk[50]), "r"(pk[51]), "r"(pk[52]), "r"(pk[53]), "r"(pk[54]), "r"(pk[55]), "r"(pk[56]), "r"(pk[57]), "r"(pk[58]), "r"(pk[59]), "r"(pk[60]), "r"(pk[61]), "r"(pk[62]), "r"(pk[63])
                 : "memory");
}

__device__ __forceinline__ void store_part4(uint8_t* d0, int p, const uint32_t (&pk)[64]) {
    asm volatile("{\n.reg .b64 d1;\nxor.b64 d1, %0, 64;\n"
                 "TS: .branchtargets P0, P1, P2, P3;\n"
                 "brx.idx.uni %1, TS;\n"
                 "P0:\n st.global.cg.v4.u32 [%0 + 0], {%2, %3, %4, %5};\n st.global.cg.v4.u32 [d1 + 0], {%10, %11, %12, %13};\n bra.uni DONE;\n"
                 "P1:\n st.global.cg.v4.u32 [%0 + 1024], {%6, %7, %8, %9};\n st.global.cg.v4.u32 [d1 + 1024], {%14, %15, %16, %17};\n bra.uni DONE;\n"
                 "P2:\n st.global.cg.v4.u32 [%0 + 16384], {%18, %19, %20, %21};\n st.global.cg.v4.u32 [d1 + 16384], {%26, %27, %28, %29};\n bra.uni DONE;\n"
                 "P3:\n st.global.cg.v4.u32 [%0 + 17408], {%22, %23, %24, %25};\n st.global.cg.v4.u32 [d1 + 17408], {%30, %31, %32, %33};\n bra.uni DONE;\n"
                 "DONE:\n}\n"
                 ::"l"(d0), "r"(p), "r"(pk[0]), "r"(pk[1]), "r"(pk[2]), "r"(pk[3]), "r"(pk[4]), "r"(pk[5]), "r"(pk[6]), "r"(pk[7]), "r"(pk[8]), "r"(pk[9]), "r"(pk[10]), "r"(pk[11]), "r"(pk[12]), "r"(pk[13]), "r"(pk[14]), "r"(pk[15]), "r"(pk[16]), "r"(pk[17]), "r"(pk[18]), "r"(pk[19]), "r"(pk[20]), "r"(pk[21]), "r"(pk[22]), "r"(pk[23]), "r"(pk[24]), "r"(pk[25]), "r"(pk[26]), "r"(pk[27]), "r"(pk[28]), "r"(pk[29]), "r"(pk[30]), "r"(pk[31])
                 : "memory");
}

__device__ __forceinline__ void set_quad(uint32_t (&d)[32], int p, uint32_t u0, uint32_t u1, uint32_t u2, uint32_t u3) {
    asm volatile("{\nTG: .branchtargets G0, G1, G2, G3, G4, G5, G6, G7;\n"
                 "brx.idx.uni %32, TG;\n"
                 "G0:\n mov.b32 %0, %33;\n mov.b32 %1, %34;\n mov.b32 %2, %35;\n mov.b32 %3, %36;\n bra.uni DONE;\n"
                 "G1:\n mov.b32 %4, %33;\n mov.b32 %5, %34;\n mov.b32 %6, %35;\n mov.b32 %7, %36;\n bra.uni DONE;\n"
                 "G2:\n mov.b32 %8, %33;\n mov.b32 %9, %34;\n mov.b32 %10, %35;\n mov.b32 %11, %36;\n bra.uni DONE;\n"
                 "G3:\n mov.b32 %12, %33;\n mov.b32 %13, %34;\n mov.b32 %14, %35;\n mov.b32 %15, %36;\n bra.uni DONE;\n"
                 "G4:\n mov.b32 %16, %33;\n mov.b32 %17, %34;\n mov.b32 %18, %35;\n mov.b32 %19, %36;\n bra.uni DONE;\n"
                 "G5:\n mov.b32 %20, %33;\n mov.b32 %21, %34;\n mov.b32 %22, %35;\n mov.b32 %23, %36;\n bra.uni DONE;\n"
                 "G6:\n mov.b32 %24, %33;\n mov.b32 %25, %34;\n mov.b32 %26, %35;\n mov.b32 %27, %36;\n bra.uni DONE;\n"
                 "G7:\n mov.b32 %28, %33;\n mov.b32 %29, %34;\n mov.b32 %30, %35;\n mov.b32 %31, %36;\n bra.uni DONE;\n"
                 "DONE:\n}\n"
                 : "+r"(d[0]), "+r"(d[1]), "+r"(d[2]), "+r"(d[3]), "+r"(d[4]), "+r"(d[5]), "+r"(d[6]), "+r"(d[7]), "+r"(d[8]), "+r"(d[9]), "+r"(d[10]), "+r"(d[11]), "+r"(d[12]), "+r"(d[13]), "+r"(d[14]), "+r"(d[15]), "+r"(d[16]), "+r"(d[17]), "+r"(d[18]), "+r"(d[19]), "+r"(d[20]), "+r"(d[21]), "+r"(d[22]), "+r"(d[23]), "+r"(d[24]), "+r"(d[25]), "+r"(d[26]), "+r"(d[27]), "+r"(d[28]), "+r"(d[29]), "+r"(d[30]), "+r"(d[31])
                 : "r"(p), "r"(u0), "r"(u1), "r"(u2), "r"(u3));
}

__device__ __forceinline__ void consumer(uint32_t sb, int pair, int c, const CUtensorMap* m_out, const uint8_t* x) {
    const int tid = threadIdx.x;
    const int warp = __shfl_sync(~0u, tid >> 5, 0);
    const int w = warp >> 2, v = warp & 3, lane = tid & 31;
    constexpr uint64_t desc_hi = ((uint64_t)(1024 >> 4) << 32) | (1ull << 62);

    const uint32_t empty_rel = lane == 2 ? mapa(sb + BAR_EMPTYL, c) : mapa(sb + BAR_EMPTY, lane & 1);
    auto release = [&](uint32_t grp) {
        if (lane < 3) mbar_arrive_cluster(empty_rel + (grp & 7) * 8);
    };
    auto wait_full = [&](uint32_t grp) { mbar_wait(sb + BAR_FULL + (grp & 7) * 8, (grp >> 3) & 1); };

    uint32_t g = 0;
    const uint32_t stg = sb + SM_REGION + w * PAGE + v * 2048;
    const uint32_t chunk0 = (lane >> 2) * 128 + (((lane & 3) ^ (lane >> 2)) << 4);
    uint32_t ndone = 0;
    auto mark_done = [&]() {
        __syncwarp();
        if (lane == 0) mbar_arrive(sb + BAR_DONE + ndone);
        ndone ^= 8;
    };
    auto ctx_dst = [&](int rnd, int seg) {
        const int rb = query_rowblock(pair, c, w, seg);
        return ptr_off(g_ctx, ((rb >> 1) * 64 + (rnd * 16 + (pair >> 2)) * 2) * PAGE + (rb & 1) * 8192 + v * 2048);
    };

    uint32_t ctl_tab;
    {
        const int t = lane, firstB = 2 * attn_rowblock(pair, 0) + 2 - w;
        auto is_half = [&](int u) { return (u == firstB - 1 || u == 16) && c == (u >= firstB); };
        const bool diag = t == firstB - 1 || t == 16;
        const int kadv = (t == 0 ? 1 : 2) + ((w == 1 && t == firstB - 1) ? 2 : 0);
        const int vadv = 2 + ((w == 1 && t == firstB) ? 2 : 0) - ((w == 1 && t == 16) ? 1 : 0);
        ctl_tab = (t == 0 ? CTL_START : 0) | (t == firstB ? CTL_SWITCH : 0) |
                  (diag ? (is_half(t) ? CTL_HALF : CTL_MASKHI) : 0) | (t == firstB - 1 ? (t ? CTL_LOADQ : CTL_DIRECT) : 0) |
                  ((t > 0 && is_half(t - 1)) ? CTL_PVHALF : 0) | ((t == 1 || t == firstB + 1) ? 0 : CTL_PVACC) |
                  (kadv << 16) | (vadv << 20);
    }

    uint32_t pk[64];
#pragma unroll
    for (int i = 0; i < 64; i++) pk[i] = 0;
    uint8_t* pend = nullptr;
    auto write_part = [&](int p) { store_part(pend, p, pk); };
    if (w == 1) bar_arrive(2, 256);
    asm volatile("barrier.cluster.wait.aligned;" ::: "memory");
    {
        const uint8_t* src = ptr_off(x, ((pair * 2 + c) * 16 + warp * 2) * (DM * 2) + lane * 16);
#pragma unroll
        for (int i = 0; i < 5; i++) {
            uint4 t;
            asm volatile("ld.global.cg.v4.u32 {%0, %1, %2, %3}, [%4];" : "=r"(t.x), "=r"(t.y), "=r"(t.z), "=r"(t.w) : "l"(src + i * 512) : "memory");
            pk[4 * i] = t.x; pk[4 * i + 1] = t.y; pk[4 * i + 2] = t.z; pk[4 * i + 3] = t.w;
        }
    }
    asm volatile("cp.async.wait_all;" ::: "memory");
    fence_async_smem();
    bar_sync(4, 256);

    float O[64], l[2] = {0.f, 0.f};
    auto finish_attention = [&](int rnd, uint32_t ge) {
        const float i0 = rcp_approx(quad_sum(l[0])), i1 = rcp_approx(quad_sum(l[1]));
        if (rnd) wg_wait<1>(); else wg_wait<0>();
        reg_fence(O);
        if (w == 0) release(ge - 2);
        release(ge - 1);
#pragma unroll
        for (int i = 0; i < 32; i++) {
            const float sc = (i & 4) ? i1 : i0;
            pk[i] = pack_bf16(O[chunk_src(i)] * sc, O[chunk_src(i) + 1] * sc);
        }
        pend = ptr_off(ctx_dst(rnd, 1), chunk0);
#pragma unroll
        for (int i = 32; i < 64; i++) pk[i] = 0;
    };
    for (int item = 0;; item++) {
        if (item != 2 && item != 5) {
            constexpr int nk = DC / 64;
            float acc[128];
            auto issue_kblock = [&](int first_acc) {
                wait_full(g);
                const uint32_t pg = sb + (g & 3) * (3 * PAGE);
                const uint64_t da = make_desc(pg + w * 8192, 16), db = make_desc(pg + PAGE, 16);
                wg_fence();
#pragma unroll
                for (int q = 0; q < 4; q++) wgmma_n256_ss(acc, da + 128 * q, db + 2 * q, q ? 1 : first_acc);
                wg_commit();
                g++;
            };
            if (item == 0) PROF(17, w);
            issue_kblock(0);
            if (item == 0) PROF(1, w);
            if (item == 0 && w == 0) PROF_GT(1);
            const int nparts = item == 0 ? 0 : (item == 3 ? 4 : 8);
            const int ln_row = (pair * 2 + c) * 16 + warp * 2;
            if (item == 0) {
                const uint8_t* src = ptr_off(x, ln_row * (DM * 2) + lane * 16);
#pragma unroll
                for (int i = 5; i < 8; i++) {
                    const uint4 t = __ldcg(reinterpret_cast<const uint4*>(src + i * 512));
                    pk[4 * i] = t.x; pk[4 * i + 1] = t.y; pk[4 * i + 2] = t.z; pk[4 * i + 3] = t.w;
                }
            }
#pragma unroll 1
            for (int kb = 1; kb < nk; kb++) {
                if (kb == nk - 2 && w == 1) bar_sync(4, 256);
                issue_kblock(1);
                if (kb == nk - 1 && w == 0) bar_arrive(4, 256);
                if (kb <= nparts) {
                    if (item == 4 && kb == 1) mbar_wait(sb + BAR_DEP + 16, 0);
                    write_part(kb - 1);
                    if (kb == nk - 1) write_part(nk - 1);
                    if (kb == nparts || kb == nk - 1) mark_done();
                }
                wg_wait<1>();
                release(g - 2);
                if (g >= 4 && g <= 8) {
                    float s[2], q[2];
                    if (g == 4) {
                        ln_sums<0>(pk, s[0], q[0]);
                        pk[32] = __float_as_uint(s[0]); pk[33] = __float_as_uint(q[0]);
                    }
                    if (g == 5) {
                        ln_sums<16>(pk, s[1], q[1]);
                        pk[34] = __float_as_uint(s[1]); pk[35] = __float_as_uint(q[1]);
                    }
                    if (g == 6) {
#pragma unroll
                        for (int r = 0; r < 2; r++) { s[r] = __uint_as_float(pk[32 + 2 * r]); q[r] = __uint_as_float(pk[33 + 2 * r]); }
                        const bool hi = lane & 16, od = lane & 8;
                        float a = hi ? s[1] : s[0], b = hi ? q[1] : q[0];
                        a += __shfl_xor_sync(~0u, hi ? s[0] : s[1], 16);
                        b += __shfl_xor_sync(~0u, hi ? q[0] : q[1], 16);
                        float t = od ? b : a;
                        t += __shfl_xor_sync(~0u, od ? a : b, 8);
#pragma unroll
                        for (int o = 4; o; o >>= 1) t += __shfl_xor_sync(~0u, t, o);
#pragma unroll
                        for (int r = 0; r < 2; r++) {
                            s[r] = __shfl_sync(~0u, t, 16 * r);
                            q[r] = __shfl_sync(~0u, t, 16 * r + 8);
                        }
                        ln_finish(s[0], q[0], pk[36], pk[37], pk[38]);
                        ln_finish(s[1], q[1], pk[39], pk[40], pk[41]);
                    }
                    if (g == 7 + w) ln_apply<0>(pk, pk[36], pk[37], pk[38], ptr_off(g_xn, image_offset(ln_row, lane)));
                    if (g == 8) {
                        ln_apply<16>(pk, pk[39], pk[40], pk[41], ptr_off(g_xn, image_offset(ln_row + 1, lane)));
                        mark_done();
                    }
                }
            }
            wg_wait<0>();
            reg_fence(acc);
            release(g - 1);
            PROF(2 + 2 * item, w);
            if (w == 0) PROF_GT(2 + 2 * item);
            const int second = item == 1 || item == 4;
            if (w == 0) {
#pragma unroll
                for (int i = 0; i < 128; i++) acc[i] *= SM_SCALE;
            }
            reg_fence(acc);
#pragma unroll
            for (int i = 0; i < 64; i++) pk[i] = pack_bf16(acc[chunk_src(i)], acc[chunk_src(i) + 1]);
            pend = ptr_off(g_kv, ((pair & 15) * 16 + (pair >> 4) * 4 + second * 2) * 65536 + w * 32768 + c * 8192 + v * 2048 + chunk0);
            PROF(3 + 2 * item, w);
            continue;
        }

        float S[64];
        auto issue_q = [&](int first_acc) {
            wait_full(g);
            const uint32_t pg = sb + (g & 3) * (3 * PAGE);
            const uint64_t da = make_desc(pg + w * 8192, 16), db = make_desc(pg + 2 * PAGE, 8192);
            const uint64_t dab = make_desc(pg + PAGE + (1 - w) * 8192, 16);
            wg_fence();
#pragma unroll
            for (int q = 0; q < 4; q++) {
                wgmma_n128_ss(S, da + 2 * q, db + 128 * q, q ? 1 : first_acc);
                wgmma_n128_ss(O, dab + 2 * q, db + 128 * q, q ? 1 : first_acc);
            }
            wg_commit();
            g++;
        };
        auto issue_half = [&](float (&A)[64], uint32_t pg, uint32_t a_off) {
            const uint64_t da = make_desc(pg + a_off, 16), db = make_desc(pg + 2 * PAGE, 8192);
#pragma unroll
            for (int q = 0; q < 4; q++) wgmma_n128_ss(A, da + 2 * q, db + 128 * q, 1);
            wg_commit();
        };
        issue_q(0);
#pragma unroll 1
        for (int kb = 1; kb < DM / 64; kb++) {
            if (kb == DM / 64 - 3 && w == 1) bar_sync(4, 256);
            const bool defer = kb >= DM / 64 - 2;
            if (!defer) {
                issue_q(1);
            } else {
                wait_full(g);
                wg_fence();
                issue_half(S, sb + (g & 3) * (3 * PAGE), w * 8192);
                g++;
            }
            if (kb == DM / 64 - 2 && w == 0) bar_arrive(4, 256);
            wg_wait<1>();
            if (kb < DM / 64 - 1) release(g - 2);
            if (kb <= 8) {
                write_part(kb - 1);
                if (kb == 8) mark_done();
            }
        }
        uint32_t Q[32], Pm[32];
#pragma unroll
        for (int i = 0; i < 32; i++) Pm[i] = 0;
        float lim = (float)(v * 16 + (lane >> 2) - 8 * (lane & 3));
        l[0] = l[1] = 0.f;
        float mc[2] = {0.f, 0.f}, scale[2] = {0.f, 0.f}, sum[4];
        uint32_t kq = g * 8, vq = g * 8, ks = 0, vs = 0, ctl;
        int t = 0;
        reg_fence(Pm);
        asm volatile("" : "+f"(lim), "+f"(mc[0]), "+f"(mc[1]), "+f"(l[0]), "+f"(l[1]), "+f"(scale[0]), "+f"(scale[1]));
        asm volatile("" : "+r"(kq), "+r"(vq), "+r"(ks), "+r"(vs), "+r"(t));
        wg_wait<0>();
        reg_fence(S);
        reg_fence(O);
        PROF(2 + 2 * item, w);
        if (w == 0) PROF_GT(2 + 2 * item);

#pragma unroll
        for (int i = 0; i < 32; i++) Q[i] = pack_bf16(S[2 * i], S[2 * i + 1]);
        const uint32_t qpark = stg + lane * 16;
        constexpr int T = 17;
        uint32_t shifted = 0;
        uint32_t tick = 0;
        constexpr uint32_t SLOT = (2 * PAGE) >> 4;
        const uint32_t kdesc0 = (uint32_t)make_desc(sb, PAGE), vdesc0 = (uint32_t)make_desc(sb, 16);
        wait_full(g);
        do {
            bar_sync(2 + w, 256);
            wg_fence();
            issue_qk(S, Q, desc_hi | (kdesc0 + ks));
            wg_commit();
            ctl = __shfl_sync(~0u, ctl_tab, t);
            mbar_wait(sb + BAR_FULL + (vq & 56), (vq >> 6) & 1);
            uint32_t krel = empty_rel + (kq & 56), vrel = empty_rel + (vq & 56);
            const uint64_t vdesc = desc_hi | (vdesc0 + vs);
            if (ctl & CTL_SWITCH) {
                scale[0] = rcp_approx(quad_sum(l[0]));
                scale[1] = rcp_approx(quad_sum(l[1]));
                l[0] = l[1] = mc[0] = mc[1] = 0.f;
                shifted = false;
                pend = ptr_off(ctx_dst(item == 5, 0), chunk0);
                asm volatile("" : "+l"(pend));
                if (w == 1) { release((kq >> 3) - 2); release((kq >> 3) + 1); }
            }
            const uint32_t kadv = (ctl >> 16) & 7, vadv = ctl >> 20;
            kq += kadv * 8; ks += kadv * SLOT; ks = ks >= 6 * SLOT ? ks - 6 * SLOT : ks;
            vq += vadv * 8; vs += vadv * SLOT; vs = vs >= 6 * SLOT ? vs - 6 * SLOT : vs;
            t++;
            uint32_t kbar = sb + BAR_FULL + (kq & 56), kpar = (kq >> 6) & 1;
            asm volatile("" : "+r"(krel), "+r"(vrel), "+r"(kbar), "+r"(kpar), "+r"(ks), "+r"(vs), "+r"(kq), "+r"(vq), "+r"(t));
            if (!(ctl & (CTL_START | CTL_PVHALF))) {
                wg_fence();
                issue_pv<0, 1>(O, Pm, vdesc, ctl & CTL_PVACC);
                wg_commit();
                issue_pv<1, 4>(O, Pm, vdesc, 1);
                wg_commit();
                issue_pv<4, 8>(O, Pm, vdesc, 1);
                wg_commit();
            } else if (ctl & CTL_PVHALF) {
                wg_fence();
                issue_pv<0, 1>(O, Pm, vdesc, ctl & CTL_PVACC);
                wg_commit();
                issue_pv<1, 4>(O, Pm, vdesc, 1);
                wg_commit();
                wg_commit();
            } else {
                wg_fence();
                issue_half(O, sb + 6 * PAGE, PAGE + (1 - w) * 8192);
                issue_half(O, sb + 9 * PAGE, PAGE + (1 - w) * 8192);
            }
            bar_arrive(3 - w, 256);
            wg_wait<2>();
            reg_fence(S);
            if (lane < 3) mbar_arrive_cluster(krel);
            if ((ctl & (CTL_HALF | CTL_MASKHI)) || shifted) {
                if (ctl & CTL_LOADQ) {
#pragma unroll
                    for (int i = 0; i < 8; i++) lds128(qpark + (i >> 2) * 8192 + (i & 3) * 512, Q[4 * i], Q[4 * i + 1], Q[4 * i + 2], Q[4 * i + 3]);
                }
                if (ctl & CTL_HALF) mask_half<0>(S, lim);
                if (ctl & CTL_MASKHI) mask_half<8>(S, lim);
                if (shifted) shift_rows(S, mc[0], mc[1]);
            }
            const bool kready = mbar_test(kbar, kpar);
            sum[0] = sum[1] = sum[2] = sum[3] = 0.f;
            float e[64];
#pragma unroll
            for (int i = 0; i < 16; i++) asm volatile("" : "+r"(Pm[i])::"memory");
            exp_stages<0, 16, 32, 4 + LAG>(S, e, Pm, sum, tick, lane < 3);
            wg_wait<0>();
            reg_fence(O);
            if (lane < 3 && !(ctl & CTL_START)) mbar_arrive_cluster(vrel);
            const bool half = ctl & CTL_HALF, first = ctl & (CTL_START | CTL_SWITCH);
#pragma unroll
            for (int i = 16; i < 32; i++) asm volatile("" : "+r"(Pm[i])::"memory");
            float limit = SUM_HI;
            float a0 = 0.f, a1 = 0.f, ta = 0.f, tb = 0.f;
            auto low_check = [&](int k) {
                auto bfly = [](float x, int m) { float r; asm volatile("shfl.sync.bfly.b32 %0, %1, %2, 0x1f, 0xffffffff;" : "=f"(r) : "f"(x), "r"(m)); return r; };
                if (k == 16 + LAG) { a0 = sum[0] + sum[1]; a1 = sum[2] + sum[3]; asm volatile("" : "+f"(a0), "+f"(a1)); }
                if (k == 17 + LAG) { ta = bfly(a0, 1); tb = bfly(a1, 1); }
                if (k == 20 + LAG) { a0 += ta; a1 += tb; asm volatile("" : "+f"(a0), "+f"(a1)); }
                if (k == 21 + LAG) { ta = bfly(a0, 2); tb = bfly(a1, 2); }
                if (k == 24 + LAG) { if (!(fminf(a0 + ta, a1 + tb) >= SUM_LO)) limit = -1.f; asm volatile("" : "+f"(limit)); }
            };
            if (!(ctl & (CTL_HALF | CTL_SWITCH | CTL_START))) {
                exp_stages<16, 32 + LAG, 32, -1>(S, e, Pm, sum, tick, lane < 3);
            } else if (half) {
                exp_stages<16, 16 + LAG, 16, -1>(S, e, Pm, sum, tick, lane < 3);
                if (ctl & CTL_START) {
                    release(g - 2); release(g - 1);
#pragma unroll
                    for (int i = 0; i < 32; i++) Q[i] = pack_bf16(O[2 * i], O[2 * i + 1]);
                    if (!(fminf(quad_sum(sum[0] + sum[1]), quad_sum(sum[2] + sum[3])) >= SUM_LO)) limit = -1.f;
                }
            } else if (ctl & CTL_START) {
                release(g - 2); release(g - 1);
                if (ctl & CTL_DIRECT) {
                    exp_stages<16, 32 + LAG, 32, -1>(S, e, Pm, sum, tick, lane < 3, [&](int k) {
                        low_check(k);
                        if (k < 32) {
#pragma unroll
                            for (int i = 2 * (k - 16); i < 2 * (k - 16) + 2; i++)
                                asm volatile("cvt.rn.bf16x2.f32 %0, %1, %2;" : "=r"(Q[i]) : "f"(O[2 * i + 1]), "f"(O[2 * i]));
                        }
                    });
                } else {
                    uint32_t u[32] = {};
                    exp_stages<16, 32 + LAG, 32, -1>(S, e, Pm, sum, tick, lane < 3, [&](int k) {
                        low_check(k);
                        if (k < 32) {
#pragma unroll
                            for (int i = 2 * (k - 16); i < 2 * (k - 16) + 2; i++)
                                asm volatile("cvt.rn.bf16x2.f32 %0, %1, %2;" : "=r"(u[i]) : "f"(O[2 * i + 1]), "f"(O[2 * i]));
                        }
                        const int i = (k - 18) >> 1;
                        if (k >= 18 && !(k & 1) && i < 8) sts128(qpark + (i >> 2) * 8192 + (i & 3) * 512, u[4 * i], u[4 * i + 1], u[4 * i + 2], u[4 * i + 3]);
                    });
                }
            } else {
                uint8_t* d[2] = {pend, (uint8_t*)((uintptr_t)pend ^ 64)};
                uint32_t po[32] = {};
                exp_stages<16, 32 + LAG, 32, -1>(S, e, Pm, sum, tick, lane < 3, [&](int k) {
                    low_check(k);
                    const int q = (k - 18) >> 1;
                    if (k >= 19 && (k & 1) && q < 8)
                        __stcg(reinterpret_cast<uint4*>(d[(q >> 1) & 1] + (q >> 2) * PAGE + (q & 1) * 1024), make_uint4(po[4 * q], po[4 * q + 1], po[4 * q + 2], po[4 * q + 3]));
                    if (k >= 32) return;
                    const int i = (k - 16) >> 1, h = (k & 1) * 2;
                    const float sc = scale[i & 1];
#pragma unroll
                    for (int r = h; r < h + 2; r++) {
                        float x0, x1;
                        asm volatile("mul.f32 %0, %1, %2;" : "=f"(x0) : "f"(O[chunk_src(4 * i + r)]), "f"(sc));
                        asm volatile("mul.f32 %0, %1, %2;" : "=f"(x1) : "f"(O[chunk_src(4 * i + r) + 1]), "f"(sc));
                        asm volatile("cvt.rn.bf16x2.f32 %0, %1, %2;" : "=r"(po[4 * i + r]) : "f"(x1), "f"(x0));
                    }
                });
                mark_done();
            }
            sum[0] += sum[1]; sum[2] += sum[3];
            float chk = sum[0] + sum[2];
            const bool bad = !(chk <= limit);
            if (__any_sync(~0u, bad)) {
                if (half) {
#pragma unroll
                    for (int i = 32; i < 64; i++) S[i] = -INFINITY;
                }
                float d0 = fmaxf(S[0], S[1]), d1 = fmaxf(S[2], S[3]);
#pragma unroll
                for (int j = 1; j < 16; j++) {
                    d0 = fmaxf(d0, fmaxf(S[4 * j], S[4 * j + 1]));
                    d1 = fmaxf(d1, fmaxf(S[4 * j + 2], S[4 * j + 3]));
                }
                d0 = fmaxf(d0, __shfl_xor_sync(~0u, d0, 1));
                d1 = fmaxf(d1, __shfl_xor_sync(~0u, d1, 1));
                d0 = fmaxf(d0, __shfl_xor_sync(~0u, d0, 2));
                d1 = fmaxf(d1, __shfl_xor_sync(~0u, d1, 2));
                if (!first) {
                    d0 = fmaxf(d0, 0.f);
                    d1 = fmaxf(d1, 0.f);
                    const float a0 = ex2(-d0), a1 = ex2(-d1);
#pragma unroll
                    for (int j = 0; j < 16; j++) {
                        O[4 * j] *= a0; O[4 * j + 1] *= a0; O[4 * j + 2] *= a1; O[4 * j + 3] *= a1;
                    }
                    l[0] *= a0; l[1] *= a1;
                }
                mc[0] += d0; mc[1] += d1;
                shifted = true;
                shift_rows(S, d0, d1);
                sum[0] = sum[1] = sum[2] = sum[3] = 0.f;
                exp_part<0, 8>(S, Pm, sum);
                exp_part<8, 16>(S, Pm, sum);
                sum[0] += sum[1]; sum[2] += sum[3];
            }
            l[0] += sum[0]; l[1] += sum[2];
            if (!kready) mbar_wait(kbar, kpar);
        } while (t < T);
        asm volatile("" : "+r"(t));
        g += 36;
        if (t > T) asm volatile("st.shared.u32 [%0], %1;" ::"r"(sb + SM_PROF), "r"(tick) : "memory");
        if (w == 0) release(g - 3);
        const uint64_t vdesc = desc_hi | (vdesc0 + vs);
        wait_full(vq >> 3);
        if (ctl & CTL_HALF) {
            wg_fence();
            issue_pv<0, 4>(O, Pm, vdesc, !(ctl & CTL_SWITCH));
            wg_commit();
        } else {
            wg_fence();
            issue_pv<0, 4>(O, Pm, vdesc, !(ctl & CTL_SWITCH));
            issue_pv<4, 8>(O, Pm, vdesc, 1);
            wg_commit();
        }
        if (item == 5) break;
        finish_attention(0, g);
        PROF(3 + 2 * item, w);
        if (w == 0) PROF_GT(3 + 2 * item);
    }

    float acc[64];
    uint32_t slot = 0;
    const uint32_t da0 = (uint32_t)make_desc(sb + w * 8192, 16), db0 = (uint32_t)make_desc(sb + PAGE, 8192);
    uint32_t da = da0, db = db0, fbar = sb + BAR_FULL + (g & 7) * 8, fpar = (g >> 3) & 1, rel = 0;
    auto issue_out = [&](int first_acc) {
        mbar_wait(fbar, fpar);
        wg_fence();
#pragma unroll
        for (int q = 0; q < 4; q++) wgmma_n128_ss(acc, (desc_hi | da) + 2 * q, (desc_hi | db) + 128 * q, q ? 1 : first_acc);
        wg_commit();
        rel = empty_rel + ((g - 1) & 7) * 8;
        g++;
        slot = slot == SM_REGION - 2 * PAGE ? 0 : slot + 2 * PAGE;
        da = da0 + (slot >> 4); db = db0 + (slot >> 4);
        fbar = sb + BAR_FULL + (g & 7) * 8; fpar = (g >> 3) & 1;
        asm volatile("" : "+r"(da), "+r"(db), "+r"(fbar), "+r"(fpar), "+r"(rel), "+r"(slot), "+r"(g));
    };
    issue_out(0);
    finish_attention(1, g - 1);
    PROF(13, w);
    if (w == 0) PROF_GT(13);
    uint32_t xr[32], gr[32];
#pragma unroll
    for (int i = 0; i < 32; i++) gr[i] = 0;
#pragma unroll 1
    for (int kb = 1; kb < 64; kb++) {
        if (kb == 60 && w == 1) bar_sync(4, 256);
        issue_out(1);
        if (kb == 63 && w == 0) bar_arrive(4, 256);
        wg_wait<1>();
        if (kb < 60 && lane < 3) mbar_arrive_cluster(rel);
        if (kb <= 8 && !(kb & 1)) {
            store_part4(pend, (kb >> 1) - 1, pk);
            if (kb == 8) mark_done();
        }
        if (kb >= 28 && kb < 60 && (kb & 3) == 2 * w) {
            uint32_t u0, u1, u2, u3;
            const int s = (kb - 28) >> 2;
            mbar_wait(sb + BAR_G + w * 8, 0);
            ldmatrix_x4(slab_addr(stg, lane, s), u0, u1, u2, u3);
            set_quad(gr, s, pack_bf16(silu_f(bf_lo(u0)), silu_f(bf_hi(u0))), pack_bf16(silu_f(bf_lo(u1)), silu_f(bf_hi(u1))),
                     pack_bf16(silu_f(bf_lo(u2)), silu_f(bf_hi(u2))), pack_bf16(silu_f(bf_lo(u3)), silu_f(bf_hi(u3))));
        }
    }
    mbar_wait(fbar, fpar);
    const uint32_t xs = sb + slot + w * PAGE + v * 2048;
#pragma unroll
    for (int s = 0; s < 8; s++) ldmatrix_x4(slab_addr(xs, lane, s), xr[4 * s], xr[4 * s + 1], xr[4 * s + 2], xr[4 * s + 3]);
    wg_wait<0>();
    reg_fence(acc);
    PROF(14, w);
    if (w == 0) PROF_GT(14);
#pragma unroll
    for (int s = 0; s < 8; s++) {
        uint32_t o[4];
#pragma unroll
        for (int k = 0; k < 4; k++)
            o[k] = bf2_add(xr[4 * s + k], bf2_mul(pack_bf16(acc[8 * s + 2 * k], acc[8 * s + 2 * k + 1]), gr[4 * s + k]));
        stmatrix_x4(slab_addr(stg, lane, s), o[0], o[1], o[2], o[3]);
        if ((s & 3) == 3) {
            fence_async_smem();
            __syncwarp();
            const int orow = ((pair >> 1) & 7) * 256 + c * 128 + w * 64 + v * 16, ocol = (pair >> 4) * 256 + (pair & 1) * 128;
            if (lane == 0) tma_store_2d(m_out, ocol + (s >> 2) * 64, orow, stg + (s >> 2) * 8192);
        }
    }
    PROF(28, w);
    if (lane == 0) {
        bulk_commit();
        bulk_wait_read();
    }
    __syncwarp();
}

__global__ void __cluster_dims__(2, 1, 1) __launch_bounds__(384, 1)
fused_kernel(const __grid_constant__ CUtensorMap m_ckv, const __grid_constant__ CUtensorMap m_wuk,
             const __grid_constant__ CUtensorMap m_wuv, const __grid_constant__ CUtensorMap m_wq,
             const __grid_constant__ CUtensorMap m_wo, const __grid_constant__ CUtensorMap m_x,
             const __grid_constant__ CUtensorMap m_out, const __grid_constant__ CUtensorMap m_gate,
             const __grid_constant__ CUtensorMap m_up, const __grid_constant__ CUtensorMap m_down, const Params P) {
    extern __shared__ __align__(1024) uint8_t smem[];
    const uint32_t sb = __shfl_sync(~0u, smem_u32(smem), 0);
    const int tid = threadIdx.x;
    const int cl = blockIdx.x >> 1, c = blockIdx.x & 1;
    const int pair = cl >= 64 ? cl : cl < 4 ? cl * 16 + 15 : cl < 36 ? ((cl - 4) >> 3) * 16 + ((cl - 4) & 7)
                                                                    : ((cl - 36) / 7) * 16 + 8 + (cl - 36) % 7;
    const int warp = __shfl_sync(~0u, tid >> 5, 0), lane = tid & 31;
    auto init_barriers = [&](int i0, int i1) {
#pragma unroll
        for (int i = i0; i < i1; i++) mbar_init(sb + SM_BAR + i * 8, (i >> 3) == 1 ? 16 : i >= 25 ? 8 : 1);
        asm volatile("fence.mbarrier_init.release.cluster;" ::: "memory");
    };
    auto finish = [&]() {
        PROF(29, tid >> 7);
        if (tid == 0) atomicAdd(&g_sync.done, 1u);
    };
    if (pair >= NMAIN / 2) {
        if (tid == 256) init_barriers(0, 16);
        if (tid == 288) *reinterpret_cast<uint32_t*>(smem + PAUSE) = 0;
        __syncthreads();
        const unsigned epoch = __ldcg(&g_sync.done) / NCTA;
        if (warp < 8) ffn_cta(smem, sb, blockIdx.x - NMAIN, epoch, P.w_r);
        else if (tid == 256) ffn_producer(sb, blockIdx.x - NMAIN, epoch + 1, &m_gate, &m_up, &m_down);
        else if (tid == 288) ffn_pacer(sb, epoch + 1);
        __syncwarp();
        finish();
    } else if (warp < 8) {
        const uint32_t r0 = tid >> 3, ch = tid & 7, dst = sb + r0 * 128 + ((ch ^ (r0 & 7)) << 4);
        const uint32_t wo = r0 * 8192 + (pair & 15) * 256 + c * 128 + ch * 16;
        const uint8_t* sw[2] = {ptr_off(P.w_uk, wo), ptr_off(P.w_uv, wo)};
        const uint8_t* sc = ptr_off(P.c_kv, ((pair >> 4) * 512 + r0) * 1024 + ch * 16);
#pragma unroll
        for (int i = 0; i < 4; i++) cp_async16(dst + i * 4096, sw[i >> 1] + (i & 1) * 262144);
#pragma unroll
        for (int i = 0; i < 8; i++) cp_async16(dst + PAGE + i * 4096, sc + i * 32768);
        asm volatile("barrier.cluster.arrive.relaxed.aligned;" ::: "memory");
        asm volatile("setmaxnreg.inc.sync.aligned.u32 240;");
        consumer(sb, pair, c, &m_out, (const uint8_t*)P.x);
        finish();
    } else {
        asm volatile("setmaxnreg.dec.sync.aligned.u32 24;");
        auto load_w = [&](int kb) {
            tma_3d(sb + kb * (3 * PAGE), &m_wuk, 0, kb * 64, (pair & 15) * 2 + c, sb + BAR_FULL + kb * 8);
            tma_3d(sb + kb * (3 * PAGE) + 8192, &m_wuv, 0, kb * 64, (pair & 15) * 2 + c, sb + BAR_FULL + kb * 8);
        };
        if (tid == 256) {
            init_barriers(0, NBAR);
            prefetch_map(&m_ckv);
            prefetch_map(&m_wuv);
            mbar_arrive(sb + BAR_FULL);
#pragma unroll 1
            for (int kb = 1; kb < 4; kb++) {
                mbar_expect_tx(sb + BAR_FULL + kb * 8, 3 * PAGE);
                if (kb <= 1) load_w(kb);
            }
        }
        PROF(18, 0);
        __syncwarp();
        cluster_sync();
        PROF(22, 0);
        if (tid == 256) {
#pragma unroll 1
            for (int kb = 1; kb < 4; kb++) {
                if (kb > 1) load_w(kb);
                tma_3d_mc(sb + kb * (3 * PAGE) + (1 + c) * PAGE, &m_ckv, 0, (pair >> 4) * 512 + c * 128, kb, sb + BAR_FULL + kb * 8);
            }
        }
        __syncwarp();
        PROF(19, 0);
        if (warp == 10) {
            sync_helper(sb, lane, pair, c);
        } else if (warp & 1) {
            fetch_helper(P.c_kv, sb, (warp >> 1) & 1, lane, pair, c);
        } else {
            producer(P, sb, pair, c, &m_ckv, &m_wuk, &m_wuv, &m_wq, &m_wo, &m_x, &m_out);
        }
    }
}

typedef CUresult (*EncodeFn)(CUtensorMap*, CUtensorMapDataType, cuuint32_t, void*, const cuuint64_t*, const cuuint64_t*,
                             const cuuint32_t*, const cuuint32_t*, CUtensorMapInterleave, CUtensorMapSwizzle,
                             CUtensorMapL2promotion, CUtensorMapFloatOOBfill);

void make_map_2d(EncodeFn fn, CUtensorMap* m, const void* ptr, int rows, int cols, int box_rows) {
    cuuint64_t dims[2] = {(cuuint64_t)cols, (cuuint64_t)rows};
    cuuint64_t strides[1] = {(cuuint64_t)cols * 2};
    cuuint32_t box[2] = {64, (cuuint32_t)box_rows};
    cuuint32_t es[2] = {1, 1};
    fn(m, CU_TENSOR_MAP_DATA_TYPE_BFLOAT16, 2, const_cast<void*>(ptr), dims, strides, box, es, CU_TENSOR_MAP_INTERLEAVE_NONE,
       CU_TENSOR_MAP_SWIZZLE_128B, CU_TENSOR_MAP_L2_PROMOTION_L2_256B, CU_TENSOR_MAP_FLOAT_OOB_FILL_NONE);
}
void make_map_w(EncodeFn fn, CUtensorMap* m, const void* ptr, int rows, int cols, int blocks, int box_rows) {
    cuuint64_t dims[3] = {64, (cuuint64_t)rows, (cuuint64_t)cols / 64};
    cuuint64_t strides[2] = {(cuuint64_t)cols * 2, 128};
    cuuint32_t box[3] = {64, (cuuint32_t)box_rows, (cuuint32_t)blocks};
    cuuint32_t es[3] = {1, 1, 1};
    fn(m, CU_TENSOR_MAP_DATA_TYPE_BFLOAT16, 3, const_cast<void*>(ptr), dims, strides, box, es, CU_TENSOR_MAP_INTERLEAVE_NONE,
       CU_TENSOR_MAP_SWIZZLE_128B, CU_TENSOR_MAP_L2_PROMOTION_L2_128B, CU_TENSOR_MAP_FLOAT_OOB_FILL_NONE);
}

void make_map_wo(EncodeFn fn, CUtensorMap* m, const void* ptr) {
    cuuint64_t dims[5] = {DM, 2, 4, 4, NH * 128 / 32};
    cuuint64_t strides[4] = {DM * 2, 8 * DM * 2, 2 * DM * 2, 32 * DM * 2};
    cuuint32_t box[5] = {64, 2, 4, 4, 2};
    cuuint32_t es[5] = {1, 1, 1, 1, 1};
    fn(m, CU_TENSOR_MAP_DATA_TYPE_BFLOAT16, 5, const_cast<void*>(ptr), dims, strides, box, es, CU_TENSOR_MAP_INTERLEAVE_NONE,
       CU_TENSOR_MAP_SWIZZLE_128B, CU_TENSOR_MAP_L2_PROMOTION_L2_256B, CU_TENSOR_MAP_FLOAT_OOB_FILL_NONE);
}

}

extern "C" void kernel_launch(void* const* d_in, const int* in_sizes, int n_in, void* d_out, int out_size) {
    static EncodeFn fn = nullptr;
    if (!fn) {
        void* f = nullptr;
        cudaDriverEntryPointQueryResult qr;
        cudaGetDriverEntryPoint("cuTensorMapEncodeTiled", &f, cudaEnableDefault, &qr);
        fn = (EncodeFn)f;
        cudaFuncSetAttribute(fused_kernel, cudaFuncAttributeMaxDynamicSharedMemorySize, SMEM_BYTES);
    }
    CUtensorMap m_ckv, m_wuk, m_wuv, m_wq, m_wo, m_x, m_out, m_gate, m_up, m_down;
    make_map_w(fn, &m_gate, d_in[8], DM, FF, FS / 64, 16);
    make_map_w(fn, &m_up, d_in[9], DM, FF, FS / 64, 16);
    make_map_w(fn, &m_down, d_in[10], FF, DM, DM / 64, 16);
    make_map_w(fn, &m_ckv, d_in[1], SEQ, DC, 1, 128);
    make_map_w(fn, &m_wq, d_in[2], DM, NH * 128, 1, 64);
    make_map_w(fn, &m_wuk, d_in[3], DC, NH * 128, 1, 64);
    make_map_w(fn, &m_wuv, d_in[4], DC, NH * 128, 1, 64);
    make_map_wo(fn, &m_wo, d_in[5]);
    make_map_w(fn, &m_x, d_in[0], SEQ, DM, 2, 64);
    make_map_2d(fn, &m_out, d_out, SEQ, DM, 16);
    Params P;
    P.x = (const __nv_bfloat16*)d_in[0];
    P.w_r = (const __nv_bfloat16*)d_in[7];
    P.c_kv = (const uint8_t*)d_in[1];
    P.w_uk = (const uint8_t*)d_in[3];
    P.w_uv = (const uint8_t*)d_in[4];
    P.w_o = (const uint8_t*)d_in[5];
    fused_kernel<<<NCTA, 384, SMEM_BYTES>>>(m_ckv, m_wuk, m_wuv, m_wq, m_wo, m_x, m_out, m_gate, m_up, m_down, P);
}
```

```cpp
#include <cuda_runtime.h>
#include <cuda_bf16.h>
#include <cuda.h>
#include <stdint.h>

namespace {

constexpr int SEQ = 2048, DM = 1024, NH = 32, DC = 512, FF = 3584;
constexpr int PAGE = 16384;
constexpr int NRING = 12;
constexpr int NCTA = 132, NMAIN = 128;
constexpr uint32_t SM_REGION = NRING * PAGE;
constexpr uint32_t SM_BAR = (NRING + 2) * PAGE;
constexpr uint32_t BAR_FULL = SM_BAR, BAR_EMPTY = SM_BAR + 64;
constexpr uint32_t BAR_DEP = SM_BAR + 128;
constexpr uint32_t BAR_G = SM_BAR + 184;
constexpr uint32_t BAR_DONE = SM_BAR + 200;
constexpr uint32_t BAR_EMPTYL = SM_BAR + 216;
constexpr int NBAR = 35;
constexpr uint32_t SM_PROF = SM_BAR + 320;
constexpr int SMEM_BYTES = SM_PROF + 512;
constexpr uint32_t SPIN_LIMIT = 1u << 16;
constexpr uint32_t POLL_MASK = 7;

struct SyncBlock {
    unsigned done;       unsigned pad0[31];
    unsigned ln;         unsigned pad1[31];
    unsigned router;     unsigned pad4[31];
    unsigned ffn_ticket; unsigned pad2[31];
    unsigned ffn_done;   unsigned pad3[31];
    unsigned kv[NH * 8];
    unsigned kvfree[16 * 8];
    unsigned ctx[32 * NH];
};

__device__ __align__(1024) uint8_t g_xn[8 * 16 * 4 * 8192];
__device__ __align__(1024) uint8_t g_kv[16 * 16 * 65536];
__device__ __align__(1024) uint8_t g_ctx[16 * 64 * 16384];
__device__ __align__(16) uint4 g_routed[2 * 128];
__device__ int g_sel[2];
__device__ __align__(16) float g_r[SEQ];
__device__ __align__(16) float g_ypart[4 * 2 * DM];
__device__ SyncBlock g_sync;

__device__ __forceinline__ uint32_t smem_u32(const void* p) { return (uint32_t)__cvta_generic_to_shared(p); }

__device__ __forceinline__ void mbar_init(uint32_t bar, uint32_t count) {
    asm volatile("mbarrier.init.shared::cta.b64 [%0], %1;" ::"r"(bar), "r"(count) : "memory");
}
#define MBAR_WAIT_ASM(HINT, LIMIT)                                                                  \
    asm volatile("{\n.reg .pred p;\n.reg .u32 n;\nmov.u32 n, 0;\n"                                  \
                 "WAIT_LOOP:\n"                                                                     \
                 "mbarrier.try_wait.parity.shared::cta.b64 p, [%0], %1" HINT ";\n"                  \
                 "@p bra WAIT_DONE;\n"                                                              \
                 "add.u32 n, n, 1;\n"                                                               \
                 "setp.lt.u32 p, n, " LIMIT ";\n"                                                   \
                 "@p bra WAIT_LOOP;\n"                                                              \
                 "WAIT_DONE:\n}\n" ::"r"(bar), "r"(parity) : "memory")
__device__ __forceinline__ void mbar_wait(uint32_t bar, uint32_t parity) { MBAR_WAIT_ASM("", "131072"); }
__device__ __forceinline__ void mbar_sleep(uint32_t bar, uint32_t parity) { MBAR_WAIT_ASM(", 2000", "8192"); }
__device__ __forceinline__ bool mbar_try(uint32_t bar, uint32_t parity) {
    uint32_t ok;
    asm volatile("{\n.reg .pred p;\nmbarrier.try_wait.parity.shared::cta.b64 p, [%1], %2;\nselp.u32 %0, 1, 0, p;\n}\n"
                 : "=r"(ok) : "r"(bar), "r"(parity) : "memory");
    return ok;
}
__device__ __forceinline__ bool mbar_test(uint32_t bar, uint32_t parity) {
    uint32_t ok;
    asm volatile("{\n.reg .pred p;\nmbarrier.test_wait.parity.shared::cta.b64 p, [%1], %2;\nselp.u32 %0, 1, 0, p;\n}\n"
                 : "=r"(ok) : "r"(bar), "r"(parity) : "memory");
    return ok;
}
__device__ __forceinline__ bool elect_one() {
    uint32_t ok;
    asm volatile("{\n.reg .pred p;\nelect.sync _|p, 0xffffffff;\nselp.u32 %0, 1, 0, p;\n}\n" : "=r"(ok));
    return ok;
}
__device__ __forceinline__ void mbar_arrive(uint32_t bar) {
    asm volatile("mbarrier.arrive.shared::cta.b64 _, [%0];" ::"r"(bar) : "memory");
}
__device__ __forceinline__ void mbar_expect_tx(uint32_t bar, uint32_t bytes) {
    asm volatile("mbarrier.arrive.expect_tx.shared::cta.b64 _, [%0], %1;" ::"r"(bar), "r"(bytes) : "memory");
}
__device__ __forceinline__ void mbar_arrive_cluster(uint32_t cluster_addr) {
    asm volatile("mbarrier.arrive.shared::cluster.b64 _, [%0];" ::"r"(cluster_addr) : "memory");
}
__device__ __forceinline__ uint32_t mapa(uint32_t addr, uint32_t rank) {
    uint32_t r;
    asm("mapa.shared::cluster.u32 %0, %1, %2;" : "=r"(r) : "r"(addr), "r"(rank));
    return r;
}
__device__ __forceinline__ void tma_3d(uint32_t dst, const CUtensorMap* m, int c0, int c1, int c2, uint32_t bar) {
    asm volatile("cp.async.bulk.tensor.3d.shared::cluster.global.mbarrier::complete_tx::bytes [%0], [%1, {%3, %4, %5}], [%2];"
                 ::"r"(dst), "l"(m), "r"(bar), "r"(c0), "r"(c1), "r"(c2) : "memory");
}
__device__ __forceinline__ void tma_3d_hint(uint32_t dst, const CUtensorMap* m, int c0, int c1, int c2, uint32_t bar, uint64_t pol) {
    asm volatile("cp.async.bulk.tensor.3d.shared::cluster.global.mbarrier::complete_tx::bytes.L2::cache_hint [%0], [%1, {%3, %4, %5}], [%2], %6;"
                 ::"r"(dst), "l"(m), "r"(bar), "r"(c0), "r"(c1), "r"(c2), "l"(pol) : "memory");
}
__device__ __forceinline__ void tma_3d_mc(uint32_t dst, const CUtensorMap* m, int c0, int c1, int c2, uint32_t bar) {
    asm volatile("cp.async.bulk.tensor.3d.shared::cluster.global.mbarrier::complete_tx::bytes.multicast::cluster [%0], [%1, {%3, %4, %5}], [%2], %6;"
                 ::"r"(dst), "l"(m), "r"(bar), "r"(c0), "r"(c1), "r"(c2), "h"((uint16_t)3) : "memory");
}
__device__ __forceinline__ void tma_5d_mc(uint32_t dst, const CUtensorMap* m, int c0, int c4, uint32_t bar) {
    asm volatile("cp.async.bulk.tensor.5d.shared::cluster.global.mbarrier::complete_tx::bytes.multicast::cluster [%0], [%1, {%3, 0, 0, 0, %4}], [%2], %5;"
                 ::"r"(dst), "l"(m), "r"(bar), "r"(c0), "r"(c4), "h"((uint16_t)3) : "memory");
}
__device__ __forceinline__ void bulk_load(uint32_t dst, const void* src, uint32_t bytes, uint32_t bar) {
    asm volatile("cp.async.bulk.shared::cluster.global.mbarrier::complete_tx::bytes [%0], [%1], %2, [%3];"
                 ::"r"(dst), "l"(src), "r"(bytes), "r"(bar) : "memory");
}
__device__ __forceinline__ void cp_async16(uint32_t dst, const void* src) {
    asm volatile("cp.async.cg.shared.global [%0], [%1], 16;" ::"r"(dst), "l"(src) : "memory");
}
__device__ __forceinline__ void bulk_load_mc(uint32_t dst, const void* src, uint32_t bytes, uint32_t bar) {
    asm volatile("cp.async.bulk.shared::cluster.global.mbarrier::complete_tx::bytes.multicast::cluster [%0], [%1], %2, [%3], %4;"
                 ::"r"(dst), "l"(src), "r"(bytes), "r"(bar), "h"((uint16_t)3) : "memory");
}
__device__ __forceinline__ void tma_store_2d(const CUtensorMap* m, int c0, int c1, uint32_t src) {
    asm volatile("cp.async.bulk.tensor.2d.global.shared::cta.bulk_group [%0, {%2, %3}], [%1];"
                 ::"l"(m), "r"(src), "r"(c0), "r"(c1) : "memory");
}
__device__ __forceinline__ void bulk_commit() { asm volatile("cp.async.bulk.commit_group;" ::: "memory"); }
__device__ __forceinline__ void bulk_wait_read() { asm volatile("cp.async.bulk.wait_group.read 0;" ::: "memory"); }
__device__ __forceinline__ void fence_async_smem() { asm volatile("fence.proxy.async.shared::cta;" ::: "memory"); }
__device__ __forceinline__ void prefetch_map(const CUtensorMap* m) {
    asm volatile("prefetch.tensormap [%0];" ::"l"(m) : "memory");
}
__device__ __forceinline__ void red_release(unsigned* p) {
    asm volatile("red.release.gpu.global.add.u32 [%0], 1;" ::"l"(p) : "memory");
}
__device__ __forceinline__ unsigned ld_relaxed(const unsigned* p) {
    unsigned v;
    asm volatile("ld.relaxed.gpu.global.u32 %0, [%1];" : "=r"(v) : "l"(p) : "memory");
    return v;
}
__device__ __forceinline__ void wait_counter(const unsigned* p, unsigned target, unsigned ns = 100) {
    for (uint32_t n = 0; (int)(ld_relaxed(p) - target) < 0 && n < SPIN_LIMIT; n++) __nanosleep(ns);
    asm volatile("fence.acquire.gpu;" ::: "memory");
    asm volatile("fence.proxy.async.global;" ::: "memory");
}
__device__ __forceinline__ void bar_sync(int id, int n) { asm volatile("bar.sync %0, %1;" ::"r"(id), "r"(n) : "memory"); }
__device__ __forceinline__ void bar_arrive(int id, int n) { asm volatile("bar.arrive %0, %1;" ::"r"(id), "r"(n) : "memory"); }
__device__ __forceinline__ void cluster_sync() {
    asm volatile("barrier.cluster.arrive.relaxed.aligned;\nbarrier.cluster.wait.aligned;" ::: "memory");
}
__device__ __forceinline__ void wg_fence() { asm volatile("wgmma.fence.sync.aligned;" ::: "memory"); }
__device__ __forceinline__ void wg_commit() { asm volatile("wgmma.commit_group.sync.aligned;" ::: "memory"); }
template <int N> __device__ __forceinline__ void wg_wait() { asm volatile("wgmma.wait_group.sync.aligned %0;" ::"n"(N) : "memory"); }
template <int N> __device__ __forceinline__ void reg_fence(float (&a)[N]) {
#pragma unroll
    for (int i = 0; i < N; i++) asm volatile("" : "+f"(a[i])::"memory");
}
template <int N> __device__ __forceinline__ void reg_fence(uint32_t (&a)[N]) {
#pragma unroll
    for (int i = 0; i < N; i++) asm volatile("" : "+r"(a[i])::"memory");
}
__device__ __forceinline__ uint32_t pack_bf16(float lo, float hi) {
    uint32_t r;
    asm("cvt.rn.bf16x2.f32 %0, %1, %2;" : "=r"(r) : "f"(hi), "f"(lo));
    return r;
}
__device__ __forceinline__ float bf_lo(uint32_t v) { return __uint_as_float(v << 16); }
__device__ __forceinline__ float bf_hi(uint32_t v) { return __uint_as_float(v & 0xffff0000u); }
__device__ __forceinline__ float bf_round(float v) { return __bfloat162float(__float2bfloat16_rn(v)); }
__device__ __forceinline__ float ex2(float v) {
    float r;
    asm("ex2.approx.ftz.f32 %0, %1;" : "=f"(r) : "f"(v));
    return r;
}
__device__ __forceinline__ float sqrt_approx(float v) {
    float r;
    asm("sqrt.approx.ftz.f32 %0, %1;" : "=f"(r) : "f"(v));
    return r;
}
__device__ __forceinline__ float rcp_approx(float v) {
    float r;
    asm("rcp.approx.ftz.f32 %0, %1;" : "=f"(r) : "f"(v));
    return r;
}
__device__ __forceinline__ float silu_f(float v) { return v * rcp_approx(1.0f + ex2(v * -1.4426950408889634f)); }
__device__ __forceinline__ void stmatrix_x4(uint32_t addr, uint32_t r0, uint32_t r1, uint32_t r2, uint32_t r3) {
    asm volatile("stmatrix.sync.aligned.m8n8.x4.shared.b16 [%0], {%1, %2, %3, %4};"
                 ::"r"(addr), "r"(r0), "r"(r1), "r"(r2), "r"(r3) : "memory");
}
__device__ __forceinline__ void sts128(uint32_t addr, uint32_t r0, uint32_t r1, uint32_t r2, uint32_t r3) {
    asm volatile("st.shared.v4.b32 [%0], {%1, %2, %3, %4};" ::"r"(addr), "r"(r0), "r"(r1), "r"(r2), "r"(r3) : "memory");
}
__device__ __forceinline__ void lds128(uint32_t addr, uint32_t& r0, uint32_t& r1, uint32_t& r2, uint32_t& r3) {
    asm volatile("ld.shared.v4.b32 {%0, %1, %2, %3}, [%4];" : "=r"(r0), "=r"(r1), "=r"(r2), "=r"(r3) : "r"(addr) : "memory");
}
__device__ __forceinline__ void ldmatrix_x4(uint32_t addr, uint32_t& r0, uint32_t& r1, uint32_t& r2, uint32_t& r3) {
    asm volatile("ldmatrix.sync.aligned.m8n8.x4.shared.b16 {%0, %1, %2, %3}, [%4];"
                 : "=r"(r0), "=r"(r1), "=r"(r2), "=r"(r3) : "r"(addr) : "memory");
}
__device__ __forceinline__ uint32_t bf2_mul(uint32_t a, uint32_t b) {
    uint32_t r;
    asm("mul.rn.bf16x2 %0, %1, %2;" : "=r"(r) : "r"(a), "r"(b));
    return r;
}
__device__ __forceinline__ uint32_t bf2_add(uint32_t a, uint32_t b) {
    uint32_t r;
    asm("add.rn.bf16x2 %0, %1, %2;" : "=r"(r) : "r"(a), "r"(b));
    return r;
}
__device__ __forceinline__ uint64_t policy_evict_first() {
    uint64_t p;
    asm("createpolicy.fractional.L2::evict_first.b64 %0, 1.0;" : "=l"(p));
    return p;
}

__device__ __forceinline__ uint64_t make_desc(uint32_t addr, uint32_t lbo_bytes) {
    return (uint64_t)((addr & 0x3FFFF) >> 4) | ((uint64_t)(lbo_bytes >> 4) << 16) | ((uint64_t)(1024 >> 4) << 32) | (1ull << 62);
}

__device__ __forceinline__ void wgmma_n256_ss(float (&d)[128], uint64_t da, uint64_t db, int acc) {
    asm volatile(
        "{\n.reg .pred p;\nsetp.ne.b32 p, %130, 0;\n"
        "wgmma.mma_async.sync.aligned.m64n256k16.f32.bf16.bf16 {"
        "%0, %1, %2, %3, %4, %5, %6, %7, %8, %9, %10, %11, %12, %13, %14, %15, "
        "%16, %17, %18, %19, %20, %21, %22, %23, %24, %25, %26, %27, %28, %29, %30, %31, "
        "%32, %33, %34, %35, %36, %37, %38, %39, %40, %41, %42, %43, %44, %45, %46, %47, "
        "%48, %49, %50, %51, %52, %53, %54, %55, %56, %57, %58, %59, %60, %61, %62, %63, "
        "%64, %65, %66, %67, %68, %69, %70, %71, %72, %73, %74, %75, %76, %77, %78, %79, "
        "%80, %81, %82, %83, %84, %85, %86, %87, %88, %89, %90, %91, %92, %93, %94, %95, "
        "%96, %97, %98, %99, %100, %101, %102, %103, %104, %105, %106, %107, %108, %109, %110, %111, "
        "%112, %113, %114, %115, %116, %117, %118, %119, %120, %121, %122, %123, %124, %125, %126, %127"
        "}, %128, %129, p, 1, 1, 1, 0;\n}\n"
        :
        "+f"(d[0]), "+f"(d[1]), "+f"(d[2]), "+f"(d[3]), "+f"(d[4]), "+f"(d[5]), "+f"(d[6]), "+f"(d[7]),
        "+f"(d[8]), "+f"(d[9]), "+f"(d[10]), "+f"(d[11]), "+f"(d[12]), "+f"(d[13]), "+f"(d[14]), "+f"(d[15]),
        "+f"(d[16]), "+f"(d[17]), "+f"(d[18]), "+f"(d[19]), "+f"(d[20]), "+f"(d[21]), "+f"(d[22]), "+f"(d[23]),
        "+f"(d[24]), "+f"(d[25]), "+f"(d[26]), "+f"(d[27]), "+f"(d[28]), "+f"(d[29]), "+f"(d[30]), "+f"(d[31]),
        "+f"(d[32]), "+f"(d[33]), "+f"(d[34]), "+f"(d[35]), "+f"(d[36]), "+f"(d[37]), "+f"(d[38]), "+f"(d[39]),
        "+f"(d[40]), "+f"(d[41]), "+f"(d[42]), "+f"(d[43]), "+f"(d[44]), "+f"(d[45]), "+f"(d[46]), "+f"(d[47]),
        "+f"(d[48]), "+f"(d[49]), "+f"(d[50]), "+f"(d[51]), "+f"(d[52]), "+f"(d[53]), "+f"(d[54]), "+f"(d[55]),
        "+f"(d[56]), "+f"(d[57]), "+f"(d[58]), "+f"(d[59]), "+f"(d[60]), "+f"(d[61]), "+f"(d[62]), "+f"(d[63]),
        "+f"(d[64]), "+f"(d[65]), "+f"(d[66]), "+f"(d[67]), "+f"(d[68]), "+f"(d[69]), "+f"(d[70]), "+f"(d[71]),
        "+f"(d[72]), "+f"(d[73]), "+f"(d[74]), "+f"(d[75]), "+f"(d[76]), "+f"(d[77]), "+f"(d[78]), "+f"(d[79]),
        "+f"(d[80]), "+f"(d[81]), "+f"(d[82]), "+f"(d[83]), "+f"(d[84]), "+f"(d[85]), "+f"(d[86]), "+f"(d[87]),
        "+f"(d[88]), "+f"(d[89]), "+f"(d[90]), "+f"(d[91]), "+f"(d[92]), "+f"(d[93]), "+f"(d[94]), "+f"(d[95]),
        "+f"(d[96]), "+f"(d[97]), "+f"(d[98]), "+f"(d[99]), "+f"(d[100]), "+f"(d[101]), "+f"(d[102]), "+f"(d[103]),
        "+f"(d[104]), "+f"(d[105]), "+f"(d[106]), "+f"(d[107]), "+f"(d[108]), "+f"(d[109]), "+f"(d[110]), "+f"(d[111]),
        "+f"(d[112]), "+f"(d[113]), "+f"(d[114]), "+f"(d[115]), "+f"(d[116]), "+f"(d[117]), "+f"(d[118]), "+f"(d[119]),
        "+f"(d[120]), "+f"(d[121]), "+f"(d[122]), "+f"(d[123]), "+f"(d[124]), "+f"(d[125]), "+f"(d[126]), "+f"(d[127])
        : "l"(da), "l"(db), "r"(acc));
}

template <int TB>
__device__ __forceinline__ void wgmma_n128_rs(float (&d)[64], uint32_t a0, uint32_t a1, uint32_t a2, uint32_t a3, uint64_t db, int acc) {
    asm volatile(
        "{\n.reg .pred p;\nsetp.ne.b32 p, %69, 0;\n"
        "wgmma.mma_async.sync.aligned.m64n128k16.f32.bf16.bf16 {"
        "%0, %1, %2, %3, %4, %5, %6, %7, %8, %9, %10, %11, %12, %13, %14, %15, "
        "%16, %17, %18, %19, %20, %21, %22, %23, %24, %25, %26, %27, %28, %29, %30, %31, "
        "%32, %33, %34, %35, %36, %37, %38, %39, %40, %41, %42, %43, %44, %45, %46, %47, "
        "%48, %49, %50, %51, %52, %53, %54, %55, %56, %57, %58, %59, %60, %61, %62, %63"
        "}, {%64, %65, %66, %67}, %68, p, 1, 1, %70;\n}\n"
        :
        "+f"(d[0]), "+f"(d[1]), "+f"(d[2]), "+f"(d[3]), "+f"(d[4]), "+f"(d[5]), "+f"(d[6]), "+f"(d[7]),
        "+f"(d[8]), "+f"(d[9]), "+f"(d[10]), "+f"(d[11]), "+f"(d[12]), "+f"(d[13]), "+f"(d[14]), "+f"(d[15]),
        "+f"(d[16]), "+f"(d[17]), "+f"(d[18]), "+f"(d[19]), "+f"(d[20]), "+f"(d[21]), "+f"(d[22]), "+f"(d[23]),
        "+f"(d[24]), "+f"(d[25]), "+f"(d[26]), "+f"(d[27]), "+f"(d[28]), "+f"(d[29]), "+f"(d[30]), "+f"(d[31]),
        "+f"(d[32]), "+f"(d[33]), "+f"(d[34]), "+f"(d[35]), "+f"(d[36]), "+f"(d[37]), "+f"(d[38]), "+f"(d[39]),
        "+f"(d[40]), "+f"(d[41]), "+f"(d[42]), "+f"(d[43]), "+f"(d[44]), "+f"(d[45]), "+f"(d[46]), "+f"(d[47]),
        "+f"(d[48]), "+f"(d[49]), "+f"(d[50]), "+f"(d[51]), "+f"(d[52]), "+f"(d[53]), "+f"(d[54]), "+f"(d[55]),
        "+f"(d[56]), "+f"(d[57]), "+f"(d[58]), "+f"(d[59]), "+f"(d[60]), "+f"(d[61]), "+f"(d[62]), "+f"(d[63])
        : "r"(a0), "r"(a1), "r"(a2), "r"(a3), "l"(db), "r"(acc), "n"(TB));
}

__device__ __forceinline__ void wgmma_n128_ss(float* d, uint64_t da, uint64_t db, int acc) {
    asm volatile(
        "{\n.reg .pred p;\nsetp.ne.b32 p, %66, 0;\n"
        "wgmma.mma_async.sync.aligned.m64n128k16.f32.bf16.bf16 {"
        "%0, %1, %2, %3, %4, %5, %6, %7, %8, %9, %10, %11, %12, %13, %14, %15, "
        "%16, %17, %18, %19, %20, %21, %22, %23, %24, %25, %26, %27, %28, %29, %30, %31, "
        "%32, %33, %34, %35, %36, %37, %38, %39, %40, %41, %42, %43, %44, %45, %46, %47, "
        "%48, %49, %50, %51, %52, %53, %54, %55, %56, %57, %58, %59, %60, %61, %62, %63"
        "}, %64, %65, p, 1, 1, 0, 1;\n}\n"
        :
        "+f"(d[0]), "+f"(d[1]), "+f"(d[2]), "+f"(d[3]), "+f"(d[4]), "+f"(d[5]), "+f"(d[6]), "+f"(d[7]),
        "+f"(d[8]), "+f"(d[9]), "+f"(d[10]), "+f"(d[11]), "+f"(d[12]), "+f"(d[13]), "+f"(d[14]), "+f"(d[15]),
        "+f"(d[16]), "+f"(d[17]), "+f"(d[18]), "+f"(d[19]), "+f"(d[20]), "+f"(d[21]), "+f"(d[22]), "+f"(d[23]),
        "+f"(d[24]), "+f"(d[25]), "+f"(d[26]), "+f"(d[27]), "+f"(d[28]), "+f"(d[29]), "+f"(d[30]), "+f"(d[31]),
        "+f"(d[32]), "+f"(d[33]), "+f"(d[34]), "+f"(d[35]), "+f"(d[36]), "+f"(d[37]), "+f"(d[38]), "+f"(d[39]),
        "+f"(d[40]), "+f"(d[41]), "+f"(d[42]), "+f"(d[43]), "+f"(d[44]), "+f"(d[45]), "+f"(d[46]), "+f"(d[47]),
        "+f"(d[48]), "+f"(d[49]), "+f"(d[50]), "+f"(d[51]), "+f"(d[52]), "+f"(d[53]), "+f"(d[54]), "+f"(d[55]),
        "+f"(d[56]), "+f"(d[57]), "+f"(d[58]), "+f"(d[59]), "+f"(d[60]), "+f"(d[61]), "+f"(d[62]), "+f"(d[63])
        : "l"(da), "l"(db), "r"(acc));
}

__device__ __forceinline__ void wgmma_n8_ta(float* d, uint64_t da, uint64_t db) {
    asm volatile("wgmma.mma_async.sync.aligned.m64n8k16.f32.bf16.bf16 {%0, %1, %2, %3}, %4, %5, 1, 1, 1, 1, 0;\n"
                 : "+f"(d[0]), "+f"(d[1]), "+f"(d[2]), "+f"(d[3]) : "l"(da), "l"(db));
}

__device__ __forceinline__ void wgmma_n8(float* d, uint64_t da, uint64_t db) {
    asm volatile("wgmma.mma_async.sync.aligned.m64n8k16.f32.bf16.bf16 {%0, %1, %2, %3}, %4, %5, 1, 1, 1, 0, 0;\n"
                 : "+f"(d[0]), "+f"(d[1]), "+f"(d[2]), "+f"(d[3]) : "l"(da), "l"(db));
}

#define PROF(slot, role)
#undef PROF_GT
#define PROF_GT(slot)

struct Params {
    const __nv_bfloat16* x;
    const __nv_bfloat16* w_r;
    const uint8_t *c_kv, *w_uk, *w_uv, *w_o;
};
__device__ __forceinline__ void lsu_prefetch(const void* p) { asm volatile("prefetch.global.L2 [%0];" ::"l"(p) : "memory"); }

template <typename T>
__device__ __forceinline__ T* ptr_off(T* base, uint32_t off) {
    uint32_t lo, hi;
    asm("mov.b64 {%0, %1}, %2;" : "=r"(lo), "=r"(hi) : "l"(base));
    asm("add.cc.u32 %0, %0, %2;\naddc.u32 %1, %1, 0;" : "+r"(lo), "+r"(hi) : "r"(off));
    T* r;
    asm("mov.b64 %0, {%1, %2};" : "=l"(r) : "r"(lo), "r"(hi));
    return r;
}
__device__ __forceinline__ int attn_rowblock(int pair, int seg) {
    int j = pair & 3, hl = pair >> 2;
    return (((hl & 1) | (j == 0)) ^ seg) ? j : 7 - j;
}
__device__ __forceinline__ int outproj_head(int i, int ib) {
    if (i < 16) return i;
    return 16 + 2 * (i & 7) + ((ib < 4) ^ ((i >> 3) & 1));
}

__device__ __forceinline__ void pin_value(uint32_t& v) { asm volatile("" : "+r"(v)); }
__device__ __forceinline__ void pin_value(int& v) { asm volatile("" : "+r"(v)); }
__device__ __forceinline__ void pin_value(const uint8_t*& v) { asm volatile("" : "+l"(v)); }

__device__ __forceinline__ void producer(const Params& P, uint32_t sb, int pair, int c,
                                         const CUtensorMap* m_ckv, const CUtensorMap* m_wuk, const CUtensorMap* m_wuv,
                                         const CUtensorMap* m_wq, const CUtensorMap* m_wo, const CUtensorMap* m_x,
                                         const CUtensorMap* m_out) {
    const int hl = pair >> 2;
    const int ibA = attn_rowblock(pair, 0), nA = 2 * ibA + 2;
    const int ib = (pair >> 1) & 7, mi = 2 * ib + c, nb = (pair >> 4) * 4 + (pair & 1) * 2;
    const bool leader = elect_one();
    uint32_t g = 4, tail = 0;
    if (leader) prefetch_map(m_wq);
    auto wait_released = [&](uint32_t need) {
#pragma unroll 1
        for (; tail <= need; tail++) mbar_wait(sb + BAR_EMPTY + (tail & 7) * 8, (tail >> 3) & 1);
    };
    auto wait_released_here = [&](uint32_t need) {
#pragma unroll 1
        for (; tail < need; tail++) mbar_wait(sb + BAR_EMPTY + (tail & 7) * 8, (tail >> 3) & 1);
        if (tail == need) mbar_wait(sb + BAR_EMPTYL + (need & 7) * 8, (need >> 3) & 1);
    };
    auto wait_released_peer = [&](uint32_t need) {
        if (tail == need) {
            uint32_t eb = sb + BAR_EMPTY + (need & 7) * 8, ep = (need >> 3) & 1;
            tail++;
            mbar_wait(eb, ep);
        }
    };
    auto full_bar = [&]() { return sb + BAR_FULL + (g & 7) * 8; };
    auto pin = [](auto&... v) { (pin_value(v), ...); };
#pragma unroll 1
    for (int rnd = 0; rnd < 2; rnd++) {
#pragma unroll 1
        for (int i = rnd ? 0 : 4; i < 16; i++) {
            const bool fresh = (i >> 2) != 2;
            int kb = (i ^ (i >> 1 & 4)) & 7, h2 = ((pair & 15) + rnd * 16) * 2 + c, krow = kb * 64, tok = (pair >> 4) * 512 + (i & 8) * 32 + c * 128;
            uint32_t pg = sb + (i & 3) * (3 * PAGE), pb = pg + (1 + c) * PAGE, bar = full_bar();
            pin(kb, h2, krow, tok, pg, pb, bar);
            const uint32_t need = g - 4 - (i < 2);
            wait_released_here(need);
            if (leader) {
                mbar_expect_tx(bar, fresh ? 3 * PAGE : 2 * PAGE);
                if (fresh) {
                    tma_3d(pg, m_wuk, 0, krow, h2, bar);
                    tma_3d(pg + 8192, m_wuv, 0, krow, h2, bar);
                }
            }
            wait_released_peer(need);
            if (leader) {
                tma_3d_mc(pb, m_ckv, 0, tok, kb, bar);
                if (rnd == 1 && i == 3) asm volatile("red.relaxed.gpu.global.add.u32 [%0], 1;" ::"l"(ptr_off(g_sync.kvfree, hl * 32)) : "memory");
            }
            g++;
        }
        mbar_sleep(sb + BAR_DEP, 0);
        const uint8_t* xa = ptr_off(g_xn, ibA * (16 * 32768) + c * PAGE);
        const uint8_t* xb = ptr_off(g_xn, (7 - ibA) * (16 * 32768) + (1 - c) * PAGE);
#pragma unroll 1
        for (int kb = 0; kb < DM / 64; kb++) {
            uint32_t pg = sb + (kb & 3) * (3 * PAGE), pw = pg + 2 * PAGE + c * 8192, bar = full_bar(), p2 = pg + PAGE;
            int krow = kb * 64;
            pin(pg, pw, p2, bar, krow);
            wait_released_here(g - 4);
            if (leader) {
                mbar_expect_tx(bar, 3 * PAGE);
                bulk_load(pg, xa, PAGE, bar);
            }
            wait_released_peer(g - 4);
            if (leader) {
                tma_3d_mc(pw, m_wq, 0, krow, (rnd * 16 + hl) * 2 + c, bar);
                bulk_load(p2, xb, PAGE, bar);
            }
            g++;
            xa += 32768;
            xb += 32768;
        }
        mbar_sleep(sb + BAR_DEP + 8 + rnd * 16, 0);
        if (rnd == 1 && leader) prefetch_map(m_wo);
        uint32_t pg = sb + c * PAGE;
#pragma unroll 1
        for (int j = 0; j < 36; j++) {
            const bool isk = j == 0 || ((j & 1) && j != 35);
            const int t = isk ? (j + 1) >> 1 : (j - 1) >> 1;
            const uint8_t* src = ptr_off(g_kv, (hl * 16 + (t >= nA ? t - nA : t)) * 65536 + (isk ? 0 : 32768) + c * PAGE);
            uint32_t bar = full_bar(), need = g - 6 + (j < 2) + (j < 5);
            pin(src, bar, need);
            wait_released(need);
            if (leader) {
                mbar_expect_tx(bar, 2 * PAGE);
                bulk_load_mc(pg, src, PAGE, bar);
            }
            g++;
            if (rnd == 0 && j >= 22 && j < 30) {
                const int cta = pair * 2 + c, i = j - 22;
                const uint32_t l = (threadIdx.x & 31) * 128;
                lsu_prefetch(ptr_off(i & 1 ? P.w_uv : P.w_uk, cta * 32768 + (i >> 1) * 8192 + 4096 + l));
            }
            if (rnd == 1 && j >= 32) {
                const int cta = pair * 2 + c, i = j - 32;
                const uint32_t l = (threadIdx.x & 31) * 128;
                lsu_prefetch(ptr_off(P.w_o, (i * 128 + cta) * 4096 + l));
            }
            pg = pg >= sb + SM_REGION - 2 * PAGE ? pg - (SM_REGION - 2 * PAGE) : pg + 2 * PAGE;
        }
    }
    uint32_t pg = sb;
#pragma unroll 1
    for (int i = 0; i < 64; i++) {
        if (i == 32 && leader) { prefetch_map(m_x); prefetch_map(m_out); }
        if ((i & 15) == 0 && i != 16) mbar_sleep(sb + BAR_DEP + 32 + (i >> 1) - (i ? 8 : 0), 0);
        const int kb = outproj_head(i >> 1, ib) * 2 + (i & 1);
        const uint8_t* src = ptr_off(g_ctx, (mi * 64 + kb) * PAGE);
        uint32_t bar = full_bar(), pw = pg + PAGE + c * 8192;
        int krow = kb * 2;
        pin(src, bar, pw, krow);
        wait_released_here(g - 6);
        if (leader) {
            mbar_expect_tx(bar, 2 * PAGE);
            bulk_load(pg, src, PAGE, bar);
        }
        wait_released_peer(g - 6);
        if (leader) tma_5d_mc(pw, m_wo, (nb + c) * 64, krow, bar);
        g++;
        pg = pg == sb + SM_REGION - 2 * PAGE ? sb : pg + 2 * PAGE;
    }
    const uint32_t bar = full_bar();
    wait_released(g - 6);
    if (leader) {
        mbar_expect_tx(bar, 2 * PAGE);
        tma_3d(pg, m_x, 0, mi * 128, nb, bar);
        tma_3d(pg + PAGE, m_x, 0, mi * 128 + 64, nb, bar);
    }
}

__device__ __forceinline__ uint32_t xn_block(int row64, int kb) {
    return (((row64 >> 2) * 16 + kb) * 4 + ((row64 & 1) * 2 + (((row64 >> 1) & 1) ^ 1))) * 8192;
}
__device__ __forceinline__ uint32_t image_offset(int row, int ch) {
    return xn_block(row >> 6, ch >> 3) + (row & 63) * 128 + (((ch & 7) ^ (row & 7)) << 4);
}
__device__ __forceinline__ uint32_t bf2_sub(uint32_t a, uint32_t b) {
    uint32_t r;
    asm("sub.rn.bf16x2 %0, %1, %2;" : "=r"(r) : "r"(a), "r"(b));
    return r;
}
__device__ __forceinline__ uint32_t bf2_fma(uint32_t a, uint32_t b, uint32_t c) {
    uint32_t r;
    asm("fma.rn.bf16x2 %0, %1, %2, %3;" : "=r"(r) : "r"(a), "r"(b), "r"(c));
    return r;
}
template <int N0, int N>
__device__ __forceinline__ void ln_sums(const uint32_t (&u)[N], float& sum, float& sq) {
    float s0 = 0.f, s1 = 0.f, q0 = 0.f, q1 = 0.f;
#pragma unroll
    for (int k = N0; k < N0 + 16; k++) {
        const float a = bf_lo(u[k]), b = bf_hi(u[k]);
        s0 += a; s1 += b;
        q0 = fmaf(a, a, q0); q1 = fmaf(b, b, q1);
    }
    sum = s0 + s1;
    sq = q0 + q1;
}
__device__ __forceinline__ void ln_finish(float sum, float sq, uint32_t& mean2, uint32_t& rhi2, uint32_t& rlo2) {
    const float ms = sum * (1.0f / DM);
    const float var = fmaxf(fmaf(-ms, ms, sq * (1.0f / DM)), 0.f);
    const float rden = rcp_approx(bf_round(sqrt_approx(bf_round(bf_round(var) + 1e-5f))));
    const float rhi = bf_round(rden);
    mean2 = pack_bf16(ms, ms);
    rhi2 = pack_bf16(rhi, rhi);
    rlo2 = pack_bf16(rden - rhi, rden - rhi);
}
template <int N0, int N>
__device__ __forceinline__ void ln_apply(const uint32_t (&u)[N], uint32_t mean2, uint32_t rhi2, uint32_t rlo2, uint8_t* dst) {
#pragma unroll
    for (int i = 0; i < 4; i++) {
        uint32_t o[4];
#pragma unroll
        for (int k = 0; k < 4; k++) {
            const uint32_t d = bf2_sub(u[N0 + 4 * i + k], mean2);
            o[k] = bf2_fma(d, rhi2, bf2_mul(d, rlo2));
        }
        __stcg(reinterpret_cast<uint4*>(dst + i * 131072), make_uint4(o[0], o[1], o[2], o[3]));
    }
}
__device__ __forceinline__ int query_rowblock(int pair, int c, int w, int seg) {
    const int qA = (w ? 0 : 2) + c;
    return 4 * attn_rowblock(pair, seg) + (seg ? 3 - qA : qA);
}

__device__ __forceinline__ void fetch_helper(const uint8_t* c_kv, uint32_t sb, int w, int lane, int pair, int c) {
    const uint32_t page = sb + SM_REGION + w * PAGE + lane * 16;
    mbar_sleep(sb + BAR_FULL + 5 * 8, 0);
    lsu_prefetch(ptr_off(c_kv, (pair >> 4) * 524288 + 262144 + ((pair & 15) * 4 + c * 2 + w) * 4096 + lane * 128));
    const unsigned e1 = __ldcg(&g_sync.done) / NCTA + 1;
#pragma unroll 1
    for (int e = 1; e <= 7; e += 2) mbar_sleep(sb + BAR_DONE + 8, (e >> 1) & 1);
    const int rb = ((pair >> 1) & 7) * 4 + c * 2 + w, kb0 = (pair >> 4) * 4 + (pair & 1) * 2;
    const uint8_t* src = ptr_off(g_xn, xn_block(rb, kb0) + lane * 16);
#pragma unroll 1
    for (int i = 0; i < 32; i += 4) {
#pragma unroll
        for (int k = 0; k < 4; k++) cp_async16(page + (i + k) * 512, src + (i + k) * 512 + (i >> 4) * (32768 - 8192));
        __nanosleep(200);
    }
    wait_counter(&g_sync.ffn_done, e1);
    const int r = __ldcg(ptr_off(g_sel, (lane >> 4) * 4)) - rb * 64, ch = lane & 15;
    const uint4 t = __ldcg(ptr_off(g_routed, ((lane >> 4) * 128 + kb0 * 8 + ch) * 16));
    asm volatile("cp.async.wait_all;" ::: "memory");
    __syncwarp();
    if (r >= 0 && r < 64)
        sts128(sb + SM_REGION + w * PAGE + (ch >> 3) * 8192 + r * 128 + (((ch & 7) ^ (r & 7)) << 4), t.x, t.y, t.z, t.w);
    __syncwarp();
    if (lane == 0) mbar_arrive(sb + BAR_G + w * 8);
    PROF(20, 2);
}

__device__ __noinline__ void sync_helper(uint32_t sb, int lane, int pair, int c) {
    const unsigned e1 = __ldcg(&g_sync.done) / NCTA + 1;
    const int ib = (pair >> 1) & 7;
    int e = 0, b = 0;
#pragma unroll 1
    for (uint32_t n = 0; (e < 9 || b < 7) && n < SPIN_LIMIT; n++) {
        if (e < 9 && __all_sync(~0u, mbar_test(sb + BAR_DONE + (e & 1) * 8, (e >> 1) & 1))) {
            const int rnd = e > 4, ev = (e - 1) & 3;
            unsigned* flag = e == 0 ? &g_sync.ln
                           : ev < 2 ? ptr_off(g_sync.kv, (rnd * 16 + (pair & 15)) * 32)
                                    : ptr_off(g_sync.ctx, (query_rowblock(pair, c, lane & 1, ev & 1) * NH + rnd * 16 + (pair >> 2)) * 4);
            asm volatile("fence.proxy.async.global;\nfence.release.gpu;" ::: "memory");
            if (lane < ((e == 0 || ev < 2) ? 1 : 2)) asm volatile("red.relaxed.gpu.global.add.u32 [%0], 1;" ::"l"(flag) : "memory");
            PROF(10 + e, 2);
            e++;
        }
        if (b < 7 && e > 0 && (b < 4 || (n & POLL_MASK) == 0)) {
            const int i = b == 4 ? lane >> 1 : 8 * b - 24 + ((lane >> 1) & 7);
            const unsigned* cnt = b == 0 ? &g_sync.ln
                                : b == 2 ? ptr_off(g_sync.kvfree, (pair & 15) * 32)
                                : b < 4 ? ptr_off(g_sync.kv, ((b >> 1) * 16 + (pair >> 2)) * 32)
                                        : ptr_off(g_sync.ctx, ((4 * ib + 2 * c + (lane & 1)) * NH + outproj_head(i & 31, ib)) * 4);
            if (__all_sync(~0u, (int)(ld_relaxed(cnt) - e1 * (b == 0 ? NMAIN : b == 2 ? 8 : b < 4 ? 16 : 1)) >= 0)) {
                asm volatile("fence.acquire.gpu;\nfence.proxy.async.global;" ::: "memory");
                __syncwarp();
                if (lane == 0) mbar_arrive(sb + BAR_DEP + b * 8);
                PROF(1 + b, 2);
                b++;
            }
        }
        __nanosleep(150);
    }
}

__device__ __forceinline__ unsigned long long block_max_key(unsigned long long k, unsigned long long* red, int tid) {
#pragma unroll
    for (int o = 16; o; o >>= 1) {
        unsigned long long t = __shfl_xor_sync(~0u, k, o);
        k = t > k ? t : k;
    }
    bar_sync(1, 256);
    if ((tid & 31) == 0) red[tid >> 5] = k;
    bar_sync(1, 256);
    k = red[0];
#pragma unroll
    for (int i = 1; i < 8; i++) k = red[i] > k ? red[i] : k;
    return k;
}

constexpr int FS = FF / 4;
constexpr int FSTAGE = 32768, FNST = 6;
constexpr int FN0 = 32, FN1 = 2 * (DM / 16), FN2 = FS / 16;
constexpr uint32_t XB = FNST * FSTAGE, HB = XB + 16384, AUX = HB + 14336, PAUSE = AUX + 192;
constexpr int PAUSE_AT = 100;

__device__ __forceinline__ void ffn_producer(uint32_t sb, int s, unsigned e1, const CUtensorMap* m_gate, const CUtensorMap* m_up,
                                             const CUtensorMap* m_down) {
    const uint64_t pol = policy_evict_first();
    int slot = 0, ph = 1;
    wait_counter(&g_sync.ln, e1 * NMAIN);
#pragma unroll 1
    for (int st = -FN0; st < FN1 + FN2; st++) {
        mbar_sleep(sb + BAR_EMPTY + slot * 8, ph);
        const uint32_t bar = sb + BAR_FULL + slot * 8;
        if (st < 0) {
            mbar_expect_tx(bar, FSTAGE);
            bulk_load(sb + slot * FSTAGE, ptr_off(g_xn, (s * FN0 + FN0 + st) * FSTAGE), FSTAGE, bar);
        } else {
            if (st >= PAUSE_AT) {
                uint32_t p;
                for (uint32_t n = 0; n < 100; n++) {
                    asm volatile("ld.volatile.shared.u32 %0, [%1];" : "=r"(p) : "r"(sb + PAUSE) : "memory");
                    if (!p) break;
                    __nanosleep(200);
                }
            }
            const bool up = st < FN1;
            mbar_expect_tx(bar, up ? FS * 32 : DM * 32);
            tma_3d_hint(sb + slot * FSTAGE, up ? ((st & 1) ? m_up : m_gate) : m_down, 0,
                        up ? (st >> 1) * 16 : s * FS + (st - FN1) * 16, up ? s * (FS / 64) : 0, bar, pol);
        }
        if (++slot == FNST) { slot = 0; ph ^= 1; }
    }
}
__device__ __forceinline__ void ffn_pacer(uint32_t sb, unsigned e1) {
    wait_counter(&g_sync.kvfree[0], e1 * 8, 500);
    asm volatile("st.volatile.shared.u32 [%0], 1;" ::"r"(sb + PAUSE) : "memory");
    wait_counter(&g_sync.kv[16 * 8], e1 * 16, 500);
    asm volatile("st.volatile.shared.u32 [%0], 0;" ::"r"(sb + PAUSE) : "memory");
}

__device__ __forceinline__ void ffn_cta(uint8_t* smem, uint32_t sb, int s, unsigned epoch, const __nv_bfloat16* w_r) {
    const int tid = threadIdx.x, lane = tid & 31;
    const int warp = __shfl_sync(~0u, tid >> 5, 0), w = warp >> 2;
    unsigned long long* red = reinterpret_cast<unsigned long long*>(smem + AUX);
    unsigned* flag = reinterpret_cast<unsigned*>(smem + AUX + 128);
    const unsigned e1 = epoch + 1;
    for (int i = tid; i < (16384 + 14336) / 16; i += 256) reinterpret_cast<uint4*>(smem + XB)[i] = make_uint4(0, 0, 0, 0);
    int slot = 0, ph = 0, prev = 0;
    auto next_stage = [&](bool has_prev) {
        wg_commit();
        wg_wait<1>();
        if (has_prev && lane < 2) mbar_arrive(sb + BAR_EMPTY + prev * 8);
        prev = slot;
        if (++slot == FNST) { slot = 0; ph ^= 1; }
    };
    {
        bar_sync(1, 256);
        if (tid < 128) *reinterpret_cast<uint4*>(smem + XB + (tid >> 3) * 1024 + (tid & 7) * 16) = __ldg(reinterpret_cast<const uint4*>(w_r) + tid);
        fence_async_smem();
        bar_sync(1, 256);
#pragma unroll 1
        for (int blk = 0; blk < 2; blk++) {
            float ar[8];
#pragma unroll
            for (int i = 0; i < 8; i++) ar[i] = 0.f;
#pragma unroll 1
            for (int kb = 0; kb < 16; kb++) {
                const uint64_t db = make_desc(sb + XB + kb * 1024, 16);
                mbar_wait(sb + BAR_FULL + slot * 8, ph);
                const uint64_t da = make_desc(sb + slot * FSTAGE + w * 16384, 16);
                wg_fence();
#pragma unroll
                for (int q = 0; q < 4; q++) {
                    wgmma_n8(ar, da + 2 * q, db + 2 * q);
                    wgmma_n8(ar + 4, da + 512 + 2 * q, db + 2 * q);
                }
                next_stage(blk + kb > 0);
            }
            wg_wait<0>();
            reg_fence(ar);
            if ((lane & 3) == 0) {
#pragma unroll
                for (int i = 0; i < 4; i++)
                    __stcg(&g_r[(s * 2 + blk) * 256 + (w + 2 - (i & 2)) * 64 + (warp & 3) * 16 + (lane >> 2) + (i & 1) * 8], bf_round(ar[2 * i]));
            }
        }
        __threadfence();
        bar_sync(1, 256);
        if (tid == 0) {
            red_release(&g_sync.router);
            wait_counter(&g_sync.router, e1 * 4);
        }
        bar_sync(1, 256);
    }
    unsigned long long keys[8];
    unsigned long long best = 0;
#pragma unroll
    for (int i = 0; i < 8; i++) {
        int idx = tid + 256 * i;
        uint32_t b = __float_as_uint(__ldcg(&g_r[idx]) + 0.0f);
        b = (b & 0x80000000u) ? ~b : (b | 0x80000000u);
        keys[i] = ((unsigned long long)b << 32) | (unsigned)(SEQ - 1 - idx);
        best = keys[i] > best ? keys[i] : best;
    }
    const unsigned long long k0 = block_max_key(best, red, tid);
    best = 0;
#pragma unroll
    for (int i = 0; i < 8; i++) best = (keys[i] != k0 && keys[i] > best) ? keys[i] : best;
    const unsigned long long k1 = block_max_key(best, red, tid);
    const int row = SEQ - 1 - (int)((w ? k1 : k0) & 0xffffffffu);
    const int ch = tid & 127;
    const uint4 xrow = __ldcg(reinterpret_cast<const uint4*>(g_xn + image_offset(row, ch)));
    *reinterpret_cast<uint4*>(smem + XB + (ch >> 3) * 1024 + w * 128 + (((ch & 7) ^ w) << 4)) = xrow;
    fence_async_smem();
    bar_sync(1, 256);
    PROF(20, tid >> 7);
    {
        float ag[28], au[28];
#pragma unroll
        for (int i = 0; i < 28; i++) ag[i] = au[i] = 0.f;
#pragma unroll 1
        for (int ks = 0; ks < DM / 16; ks++) {
            const uint64_t db = make_desc(sb + XB + (ks >> 2) * 1024 + (ks & 3) * 32, 16);
            mbar_wait(sb + BAR_FULL + slot * 8, ph);
            uint64_t da = make_desc(sb + slot * FSTAGE + w * (7 * 2048), 16);
            wg_fence();
#pragma unroll
            for (int b = 0; b < 7; b++) wgmma_n8_ta(ag + 4 * b, da + b * 128, db);
            next_stage(true);
            mbar_wait(sb + BAR_FULL + slot * 8, ph);
            da = make_desc(sb + slot * FSTAGE + w * (7 * 2048), 16);
            wg_fence();
#pragma unroll
            for (int b = 0; b < 7; b++) wgmma_n8_ta(au + 4 * b, da + b * 128, db);
            next_stage(true);
        }
        wg_wait<0>();
        reg_fence(ag);
        reg_fence(au);
        if ((lane & 3) == 0) {
#pragma unroll
            for (int i = 0; i < 28; i++) {
                const int f = (warp & 3) * 16 + (lane >> 2) + (i & 2) * 4, tok = i & 1;
                const float h = bf_round(silu_f(bf_round(ag[i]))) * bf_round(au[i]);
                *reinterpret_cast<__nv_bfloat16*>(smem + HB + (w * 7 + (i >> 2)) * 1024 + tok * 128 + (((f >> 3) ^ tok) << 4) + (f & 7) * 2) =
                    __float2bfloat16_rn(h);
            }
        }
    }
    fence_async_smem();
    bar_sync(1, 256);
    PROF(21, tid >> 7);
    {
        float ay[32];
#pragma unroll
        for (int i = 0; i < 32; i++) ay[i] = 0.f;
#pragma unroll 1
        for (int ks = 0; ks < FN2; ks++) {
            const uint64_t db = make_desc(sb + HB + (ks >> 2) * 1024 + (ks & 3) * 32, 16);
            mbar_wait(sb + BAR_FULL + slot * 8, ph);
            const uint64_t da = make_desc(sb + slot * FSTAGE + w * (8 * 2048), 16);
            wg_fence();
#pragma unroll
            for (int b = 0; b < 8; b++) wgmma_n8_ta(ay + 4 * b, da + b * 128, db);
            next_stage(true);
        }
        wg_wait<0>();
        reg_fence(ay);
        if ((lane & 3) == 0) {
#pragma unroll
            for (int i = 0; i < 32; i++)
                g_ypart[(s * 2 + (i & 1)) * DM + (w * 8 + (i >> 2)) * 64 + (warp & 3) * 16 + (lane >> 2) + (i & 2) * 4] = ay[i];
        }
    }
    PROF(23, tid >> 7);
    __threadfence();
    bar_sync(1, 256);
    if (tid == 0) {
        *flag = atomicAdd(&g_sync.ffn_ticket, 1u) == epoch * 4 + 3;
        __threadfence();
    }
    bar_sync(1, 256);
    if (*flag) {
        const float sg = bf_round(__fdividef(1.0f, 1.0f + __expf(-__ldcg(&g_r[row]))));
        const uint32_t xu[4] = {xrow.x, xrow.y, xrow.z, xrow.w};
        uint32_t o[4];
#pragma unroll
        for (int k = 0; k < 4; k++) {
            float y0 = 0.f, y1 = 0.f;
#pragma unroll
            for (int q = 0; q < 4; q++) {
                const float2 y = __ldcg(reinterpret_cast<const float2*>(&g_ypart[(q * 2 + w) * DM + ch * 8 + 2 * k]));
                y0 += y.x; y1 += y.y;
            }
            o[k] = pack_bf16(bf_lo(xu[k]) + bf_round(bf_round(y0) * sg), bf_hi(xu[k]) + bf_round(bf_round(y1) * sg));
        }
        g_routed[w * 128 + ch] = make_uint4(o[0], o[1], o[2], o[3]);
        if (ch == 0) g_sel[w] = row;
        bar_sync(1, 256);
        if (tid == 0) red_release(&g_sync.ffn_done);
    }
}

__device__ __forceinline__ uint32_t slab_addr(uint32_t stg, int lane, int s) {
    const int row = ((lane >> 3) & 1) * 8 + (lane & 7);
    const int chunk = 2 * (s & 3) + (lane >> 4);
    return stg + row * 128 + (s >> 2) * 8192 + ((chunk ^ (lane & 7)) << 4);
}

constexpr float SM_SCALE = 0.08838834764831845f * 1.4426950408889634f;
constexpr float SUM_HI = 1048576.f, SUM_LO = 1.0f / 1048576.f;

template <int J0>
__device__ __forceinline__ void mask_half(float (&S)[64], float limf) {
    asm volatile("" : "+f"(limf));
#pragma unroll
    for (int i = 0; i < 32; i++) {
        const int j = i >> 2, key = 32 * (j >> 2) + 2 * (j & 3) + (i & 1) - 4 * (i & 2);
        float t;
        asm("add.sat.f32 %0, %1, %2;" : "=f"(t) : "f"((float)key), "f"(-limf));
        S[4 * J0 + i] = fmaf(t, -1e30f, S[4 * J0 + i]);
    }
}
__device__ __forceinline__ void issue_qk(float (&S)[64], const uint32_t (&Q)[32], uint64_t d0) {
#pragma unroll
    for (int s = 0; s < 8; s++)
        wgmma_n128_rs<1>(S, Q[4 * s], Q[4 * s + 1], Q[4 * s + 2], Q[4 * s + 3], d0 + s * 128, s > 0);
}
template <int S0, int S1>
__device__ __forceinline__ void issue_pv(float (&O)[64], const uint32_t (&Pm)[32], uint64_t d0, int acc) {
#pragma unroll
    for (int s = S0; s < S1; s++)
        wgmma_n128_rs<0>(O, Pm[4 * s], Pm[4 * s + 1], Pm[4 * s + 2], Pm[4 * s + 3], d0 + (s >> 2) * (PAGE >> 4) + (s & 3) * 2, s > 0 ? 1 : acc);
}
template <int J0, int J1>
__device__ __forceinline__ void exp_part(const float (&S)[64], uint32_t (&Pm)[32], float (&sum)[4]) {
#pragma unroll
    for (int i = 2 * J0; i < 2 * J1; i++) asm volatile("" : "+r"(Pm[i])::"memory");
#pragma unroll
    for (int j = J0; j < J1; j++) {
        const float e0 = ex2(S[4 * j]), e1 = ex2(S[4 * j + 1]), e2 = ex2(S[4 * j + 2]), e3 = ex2(S[4 * j + 3]);
        sum[0] += e0; sum[1] += e1; sum[2] += e2; sum[3] += e3;
        Pm[2 * j] = pack_bf16(e0, e1);
        Pm[2 * j + 1] = pack_bf16(e2, e3);
    }
}
__device__ __forceinline__ void shift_rows(float (&S)[64], float d0, float d1) {
#pragma unroll
    for (int j = 0; j < 16; j++) {
        S[4 * j] -= d0; S[4 * j + 1] -= d0; S[4 * j + 2] -= d1; S[4 * j + 3] -= d1;
    }
}
__device__ __forceinline__ void sched_fence(uint32_t& tick, bool on) {
    asm volatile("{\n.reg .pred p;\nsetp.ne.u32 p, %1, 0;\n@p mov.u32 %0, %%clock;\n}\n" : "+r"(tick) : "r"((uint32_t)on) : "memory");
}
constexpr int LAG = 4;
struct NoExtra { __device__ __forceinline__ void operator()(int) const {} };
template <int K0, int K1, int NP, int WAITAT, typename X = NoExtra>
__device__ __forceinline__ void exp_stages(const float (&S)[64], float (&e)[64], uint32_t (&Pm)[32], float (&sum)[4], uint32_t& tick, bool on,
                                           X extra = X()) {
#pragma unroll
    for (int k = K0; k < K1; k++) {
        if (k == WAITAT) wg_wait<1>();
        if (k < NP) {
            asm volatile("ex2.approx.ftz.f32 %0, %1;" : "=f"(e[2 * k]) : "f"(S[2 * k]));
            asm volatile("ex2.approx.ftz.f32 %0, %1;" : "=f"(e[2 * k + 1]) : "f"(S[2 * k + 1]));
        }
        if (k >= LAG) {
            const int i = 2 * (k - LAG);
            asm volatile("add.f32 %0, %0, %1;" : "+f"(sum[i & 3]) : "f"(e[i]));
            asm volatile("add.f32 %0, %0, %1;" : "+f"(sum[(i & 3) + 1]) : "f"(e[i + 1]));
            asm volatile("cvt.rn.bf16x2.f32 %0, %1, %2;" : "=r"(Pm[i / 2]) : "f"(e[i + 1]), "f"(e[i]));
        }
        extra(k);
        if (k >= LAG - 1 && k < NP - 1 && k != K1 - 1) sched_fence(tick, on);
    }
}
__device__ constexpr int chunk_src(int i) { return 4 * (4 * (i >> 3) + (i & 3)) + 2 * ((i >> 2) & 1); }
enum : uint32_t { CTL_START = 1, CTL_SWITCH = 2, CTL_DIRECT = 4, CTL_HALF = 8, CTL_MASKHI = 16, CTL_LOADQ = 32, CTL_PVHALF = 64, CTL_PVACC = 128 };
__device__ __forceinline__ float quad_sum(float v) {
    v += __shfl_xor_sync(~0u, v, 1);
    return v + __shfl_xor_sync(~0u, v, 2);
}

__device__ __forceinline__ void store_part(uint8_t* d0, int p, const uint32_t (&pk)[64]) {
    asm volatile("{\n.reg .b64 d1;\nxor.b64 d1, %0, 64;\n"
                 "TS: .branchtargets P0, P1, P2, P3, P4, P5, P6, P7;\n"
                 "brx.idx.uni %1, TS;\n"
                 "P0:\n st.global.cg.v4.u32 [%0 + 0], {%2, %3, %4, %5};\n st.global.cg.v4.u32 [d1 + 0], {%10, %11, %12, %13};\n bra.uni DONE;\n"
                 "P1:\n st.global.cg.v4.u32 [%0 + 1024], {%6, %7, %8, %9};\n st.global.cg.v4.u32 [d1 + 1024], {%14, %15, %16, %17};\n bra.uni DONE;\n"
                 "P2:\n st.global.cg.v4.u32 [%0 + 16384], {%18, %19, %20, %21};\n st.global.cg.v4.u32 [d1 + 16384], {%26, %27, %28, %29};\n bra.uni DONE;\n"
                 "P3:\n st.global.cg.v4.u32 [%0 + 17408], {%22, %23, %24, %25};\n st.global.cg.v4.u32 [d1 + 17408], {%30, %31, %32, %33};\n bra.uni DONE;\n"
                 "P4:\n st.global.cg.v4.u32 [%0 + 65536], {%34, %35, %36, %37};\n st.global.cg.v4.u32 [d1 + 65536], {%42, %43, %44, %45};\n bra.uni DONE;\n"
                 "P5:\n st.global.cg.v4.u32 [%0 + 66560], {%38, %39, %40, %41};\n st.global.cg.v4.u32 [d1 + 66560], {%46, %47, %48, %49};\n bra.uni DONE;\n"
                 "P6:\n st.global.cg.v4.u32 [%0 + 81920], {%50, %51, %52, %53};\n st.global.cg.v4.u32 [d1 + 81920], {%58, %59, %60, %61};\n bra.uni DONE;\n"
                 "P7:\n st.global.cg.v4.u32 [%0 + 82944], {%54, %55, %56, %57};\n st.global.cg.v4.u32 [d1 + 82944], {%62, %63, %64, %65};\n bra.uni DONE;\n"
                 "DONE:\n}\n"
                 ::"l"(d0), "r"(p), "r"(pk[0]), "r"(pk[1]), "r"(pk[2]), "r"(pk[3]), "r"(pk[4]), "r"(pk[5]), "r"(pk[6]), "r"(pk[7]), "r"(pk[8]), "r"(pk[9]), "r"(pk[10]), "r"(pk[11]), "r"(pk[12]), "r"(pk[13]), "r"(pk[14]), "r"(pk[15]), "r"(pk[16]), "r"(pk[17]), "r"(pk[18]), "r"(pk[19]), "r"(pk[20]), "r"(pk[21]), "r"(pk[22]), "r"(pk[23]), "r"(pk[24]), "r"(pk[25]), "r"(pk[26]), "r"(pk[27]), "r"(pk[28]), "r"(pk[29]), "r"(pk[30]), "r"(pk[31]), "r"(pk[32]), "r"(pk[33]), "r"(pk[34]), "r"(pk[35]), "r"(pk[36]), "r"(pk[37]), "r"(pk[38]), "r"(pk[39]), "r"(pk[40]), "r"(pk[41]), "r"(pk[42]), "r"(pk[43]), "r"(pk[44]), "r"(pk[45]), "r"(pk[46]), "r"(pk[47]), "r"(pk[48]), "r"(pk[49]), "r"(pk[50]), "r"(pk[51]), "r"(pk[52]), "r"(pk[53]), "r"(pk[54]), "r"(pk[55]), "r"(pk[56]), "r"(pk[57]), "r"(pk[58]), "r"(pk[59]), "r"(pk[60]), "r"(pk[61]), "r"(pk[62]), "r"(pk[63])
                 : "memory");
}

__device__ __forceinline__ void store_part4(uint8_t* d0, int p, const uint32_t (&pk)[64]) {
    asm volatile("{\n.reg .b64 d1;\nxor.b64 d1, %0, 64;\n"
                 "TS: .branchtargets P0, P1, P2, P3;\n"
                 "brx.idx.uni %1, TS;\n"
                 "P0:\n st.global.cg.v4.u32 [%0 + 0], {%2, %3, %4, %5};\n st.global.cg.v4.u32 [d1 + 0], {%10, %11, %12, %13};\n bra.uni DONE;\n"
                 "P1:\n st.global.cg.v4.u32 [%0 + 1024], {%6, %7, %8, %9};\n st.global.cg.v4.u32 [d1 + 1024], {%14, %15, %16, %17};\n bra.uni DONE;\n"
                 "P2:\n st.global.cg.v4.u32 [%0 + 16384], {%18, %19, %20, %21};\n st.global.cg.v4.u32 [d1 + 16384], {%26, %27, %28, %29};\n bra.uni DONE;\n"
                 "P3:\n st.global.cg.v4.u32 [%0 + 17408], {%22, %23, %24, %25};\n st.global.cg.v4.u32 [d1 + 17408], {%30, %31, %32, %33};\n bra.uni DONE;\n"
                 "DONE:\n}\n"
                 ::"l"(d0), "r"(p), "r"(pk[0]), "r"(pk[1]), "r"(pk[2]), "r"(pk[3]), "r"(pk[4]), "r"(pk[5]), "r"(pk[6]), "r"(pk[7]), "r"(pk[8]), "r"(pk[9]), "r"(pk[10]), "r"(pk[11]), "r"(pk[12]), "r"(pk[13]), "r"(pk[14]), "r"(pk[15]), "r"(pk[16]), "r"(pk[17]), "r"(pk[18]), "r"(pk[19]), "r"(pk[20]), "r"(pk[21]), "r"(pk[22]), "r"(pk[23]), "r"(pk[24]), "r"(pk[25]), "r"(pk[26]), "r"(pk[27]), "r"(pk[28]), "r"(pk[29]), "r"(pk[30]), "r"(pk[31])
                 : "memory");
}

__device__ __forceinline__ void set_quad(uint32_t (&d)[32], int p, uint32_t u0, uint32_t u1, uint32_t u2, uint32_t u3) {
    asm volatile("{\nTG: .branchtargets G0, G1, G2, G3, G4, G5, G6, G7;\n"
                 "brx.idx.uni %32, TG;\n"
                 "G0:\n mov.b32 %0, %33;\n mov.b32 %1, %34;\n mov.b32 %2, %35;\n mov.b32 %3, %36;\n bra.uni DONE;\n"
                 "G1:\n mov.b32 %4, %33;\n mov.b32 %5, %34;\n mov.b32 %6, %35;\n mov.b32 %7, %36;\n bra.uni DONE;\n"
                 "G2:\n mov.b32 %8, %33;\n mov.b32 %9, %34;\n mov.b32 %10, %35;\n mov.b32 %11, %36;\n bra.uni DONE;\n"
                 "G3:\n mov.b32 %12, %33;\n mov.b32 %13, %34;\n mov.b32 %14, %35;\n mov.b32 %15, %36;\n bra.uni DONE;\n"
                 "G4:\n mov.b32 %16, %33;\n mov.b32 %17, %34;\n mov.b32 %18, %35;\n mov.b32 %19, %36;\n bra.uni DONE;\n"
                 "G5:\n mov.b32 %20, %33;\n mov.b32 %21, %34;\n mov.b32 %22, %35;\n mov.b32 %23, %36;\n bra.uni DONE;\n"
                 "G6:\n mov.b32 %24, %33;\n mov.b32 %25, %34;\n mov.b32 %26, %35;\n mov.b32 %27, %36;\n bra.uni DONE;\n"
                 "G7:\n mov.b32 %28, %33;\n mov.b32 %29, %34;\n mov.b32 %30, %35;\n mov.b32 %31, %36;\n bra.uni DONE;\n"
                 "DONE:\n}\n"
                 : "+r"(d[0]), "+r"(d[1]), "+r"(d[2]), "+r"(d[3]), "+r"(d[4]), "+r"(d[5]), "+r"(d[6]), "+r"(d[7]), "+r"(d[8]), "+r"(d[9]), "+r"(d[10]), "+r"(d[11]), "+r"(d[12]), "+r"(d[13]), "+r"(d[14]), "+r"(d[15]), "+r"(d[16]), "+r"(d[17]), "+r"(d[18]), "+r"(d[19]), "+r"(d[20]), "+r"(d[21]), "+r"(d[22]), "+r"(d[23]), "+r"(d[24]), "+r"(d[25]), "+r"(d[26]), "+r"(d[27]), "+r"(d[28]), "+r"(d[29]), "+r"(d[30]), "+r"(d[31])
                 : "r"(p), "r"(u0), "r"(u1), "r"(u2), "r"(u3));
}

__device__ __forceinline__ void consumer(uint32_t sb, int pair, int c, const CUtensorMap* m_out, const uint8_t* x) {
    const int tid = threadIdx.x;
    const int warp = __shfl_sync(~0u, tid >> 5, 0);
    const int w = warp >> 2, v = warp & 3, lane = tid & 31;
    constexpr uint64_t desc_hi = ((uint64_t)(1024 >> 4) << 32) | (1ull << 62);

    const uint32_t empty_rel = lane == 2 ? mapa(sb + BAR_EMPTYL, c) : mapa(sb + BAR_EMPTY, lane & 1);
    auto release = [&](uint32_t grp) {
        if (lane < 3) mbar_arrive_cluster(empty_rel + (grp & 7) * 8);
    };
    auto wait_full = [&](uint32_t grp) { mbar_wait(sb + BAR_FULL + (grp & 7) * 8, (grp >> 3) & 1); };

    uint32_t g = 0;
    const uint32_t stg = sb + SM_REGION + w * PAGE + v * 2048;
    const uint32_t chunk0 = (lane >> 2) * 128 + (((lane & 3) ^ (lane >> 2)) << 4);
    uint32_t ndone = 0;
    auto mark_done = [&]() {
        __syncwarp();
        if (lane == 0) mbar_arrive(sb + BAR_DONE + ndone);
        ndone ^= 8;
    };
    auto ctx_dst = [&](int rnd, int seg) {
        const int rb = query_rowblock(pair, c, w, seg);
        return ptr_off(g_ctx, ((rb >> 1) * 64 + (rnd * 16 + (pair >> 2)) * 2) * PAGE + (rb & 1) * 8192 + v * 2048);
    };

    uint32_t ctl_tab;
    {
        const int t = lane, firstB = 2 * attn_rowblock(pair, 0) + 2 - w;
        auto is_half = [&](int u) { return (u == firstB - 1 || u == 16) && c == (u >= firstB); };
        const bool diag = t == firstB - 1 || t == 16;
        const int kadv = (t == 0 ? 1 : 2) + ((w == 1 && t == firstB - 1) ? 2 : 0);
        const int vadv = 2 + ((w == 1 && t == firstB) ? 2 : 0) - ((w == 1 && t == 16) ? 1 : 0);
        ctl_tab = (t == 0 ? CTL_START : 0) | (t == firstB ? CTL_SWITCH : 0) |
                  (diag ? (is_half(t) ? CTL_HALF : CTL_MASKHI) : 0) | (t == firstB - 1 ? (t ? CTL_LOADQ : CTL_DIRECT) : 0) |
                  ((t > 0 && is_half(t - 1)) ? CTL_PVHALF : 0) | ((t == 1 || t == firstB + 1) ? 0 : CTL_PVACC) |
                  (kadv << 16) | (vadv << 20);
    }

    uint32_t pk[64];
#pragma unroll
    for (int i = 0; i < 64; i++) pk[i] = 0;
    uint8_t* pend = nullptr;
    auto write_part = [&](int p) { store_part(pend, p, pk); };
    if (w == 1) bar_arrive(2, 256);
    asm volatile("barrier.cluster.wait.aligned;" ::: "memory");
    {
        const uint8_t* src = ptr_off(x, ((pair * 2 + c) * 16 + warp * 2) * (DM * 2) + lane * 16);
#pragma unroll
        for (int i = 0; i < 5; i++) {
            uint4 t;
            asm volatile("ld.global.cg.v4.u32 {%0, %1, %2, %3}, [%4];" : "=r"(t.x), "=r"(t.y), "=r"(t.z), "=r"(t.w) : "l"(src + i * 512) : "memory");
            pk[4 * i] = t.x; pk[4 * i + 1] = t.y; pk[4 * i + 2] = t.z; pk[4 * i + 3] = t.w;
        }
    }
    asm volatile("cp.async.wait_all;" ::: "memory");
    fence_async_smem();
    bar_sync(4, 256);

    float O[64], l[2] = {0.f, 0.f};
    auto finish_attention = [&](int rnd, uint32_t ge) {
        const float i0 = rcp_approx(quad_sum(l[0])), i1 = rcp_approx(quad_sum(l[1]));
        if (rnd) wg_wait<1>(); else wg_wait<0>();
        reg_fence(O);
        if (w == 0) release(ge - 2);
        release(ge - 1);
#pragma unroll
        for (int i = 0; i < 32; i++) {
            const float sc = (i & 4) ? i1 : i0;
            pk[i] = pack_bf16(O[chunk_src(i)] * sc, O[chunk_src(i) + 1] * sc);
        }
        pend = ptr_off(ctx_dst(rnd, 1), chunk0);
#pragma unroll
        for (int i = 32; i < 64; i++) pk[i] = 0;
    };
    for (int item = 0;; item++) {
        if (item != 2 && item != 5) {
            constexpr int nk = DC / 64;
            float acc[128];
            auto issue_kblock = [&](int first_acc) {
                wait_full(g);
                const uint32_t pg = sb + (g & 3) * (3 * PAGE);
                const uint64_t da = make_desc(pg + w * 8192, 16), db = make_desc(pg + PAGE, 16);
                wg_fence();
#pragma unroll
                for (int q = 0; q < 4; q++) wgmma_n256_ss(acc, da + 128 * q, db + 2 * q, q ? 1 : first_acc);
                wg_commit();
                g++;
            };
            if (item == 0) PROF(17, w);
            issue_kblock(0);
            if (item == 0) PROF(1, w);
            if (item == 0 && w == 0) PROF_GT(1);
            const int nparts = item == 0 ? 0 : (item == 3 ? 4 : 8);
            const int ln_row = (pair * 2 + c) * 16 + warp * 2;
            if (item == 0) {
                const uint8_t* src = ptr_off(x, ln_row * (DM * 2) + lane * 16);
#pragma unroll
                for (int i = 5; i < 8; i++) {
                    const uint4 t = __ldcg(reinterpret_cast<const uint4*>(src + i * 512));
                    pk[4 * i] = t.x; pk[4 * i + 1] = t.y; pk[4 * i + 2] = t.z; pk[4 * i + 3] = t.w;
                }
            }
#pragma unroll 1
            for (int kb = 1; kb < nk; kb++) {
                if (kb == nk - 2 && w == 1) bar_sync(4, 256);
                issue_kblock(1);
                if (kb == nk - 1 && w == 0) bar_arrive(4, 256);
                if (kb <= nparts) {
                    if (item == 4 && kb == 1) mbar_wait(sb + BAR_DEP + 16, 0);
                    write_part(kb - 1);
                    if (kb == nk - 1) write_part(nk - 1);
                    if (kb == nparts || kb == nk - 1) mark_done();
                }
                wg_wait<1>();
                release(g - 2);
                if (g >= 4 && g <= 8) {
                    float s[2], q[2];
                    if (g == 4) {
                        ln_sums<0>(pk, s[0], q[0]);
                        pk[32] = __float_as_uint(s[0]); pk[33] = __float_as_uint(q[0]);
                    }
                    if (g == 5) {
                        ln_sums<16>(pk, s[1], q[1]);
                        pk[34] = __float_as_uint(s[1]); pk[35] = __float_as_uint(q[1]);
                    }
                    if (g == 6) {
#pragma unroll
                        for (int r = 0; r < 2; r++) { s[r] = __uint_as_float(pk[32 + 2 * r]); q[r] = __uint_as_float(pk[33 + 2 * r]); }
                        const bool hi = lane & 16, od = lane & 8;
                        float a = hi ? s[1] : s[0], b = hi ? q[1] : q[0];
                        a += __shfl_xor_sync(~0u, hi ? s[0] : s[1], 16);
                        b += __shfl_xor_sync(~0u, hi ? q[0] : q[1], 16);
                        float t = od ? b : a;
                        t += __shfl_xor_sync(~0u, od ? a : b, 8);
#pragma unroll
                        for (int o = 4; o; o >>= 1) t += __shfl_xor_sync(~0u, t, o);
#pragma unroll
                        for (int r = 0; r < 2; r++) {
                            s[r] = __shfl_sync(~0u, t, 16 * r);
                            q[r] = __shfl_sync(~0u, t, 16 * r + 8);
                        }
                        ln_finish(s[0], q[0], pk[36], pk[37], pk[38]);
                        ln_finish(s[1], q[1], pk[39], pk[40], pk[41]);
                    }
                    if (g == 7 + w) ln_apply<0>(pk, pk[36], pk[37], pk[38], ptr_off(g_xn, image_offset(ln_row, lane)));
                    if (g == 8) {
                        ln_apply<16>(pk, pk[39], pk[40], pk[41], ptr_off(g_xn, image_offset(ln_row + 1, lane)));
                        mark_done();
                    }
                }
            }
            wg_wait<0>();
            reg_fence(acc);
            release(g - 1);
            PROF(2 + 2 * item, w);
            if (w == 0) PROF_GT(2 + 2 * item);
            const int second = item == 1 || item == 4;
            if (w == 0) {
#pragma unroll
                for (int i = 0; i < 128; i++) acc[i] *= SM_SCALE;
            }
            reg_fence(acc);
#pragma unroll
            for (int i = 0; i < 64; i++) pk[i] = pack_bf16(acc[chunk_src(i)], acc[chunk_src(i) + 1]);
            pend = ptr_off(g_kv, ((pair & 15) * 16 + (pair >> 4) * 4 + second * 2) * 65536 + w * 32768 + c * 8192 + v * 2048 + chunk0);
            PROF(3 + 2 * item, w);
            continue;
        }

        float S[64];
        auto issue_q = [&](int first_acc) {
            wait_full(g);
            const uint32_t pg = sb + (g & 3) * (3 * PAGE);
            const uint64_t da = make_desc(pg + w * 8192, 16), db = make_desc(pg + 2 * PAGE, 8192);
            const uint64_t dab = make_desc(pg + PAGE + (1 - w) * 8192, 16);
            wg_fence();
#pragma unroll
            for (int q = 0; q < 4; q++) {
                wgmma_n128_ss(S, da + 2 * q, db + 128 * q, q ? 1 : first_acc);
                wgmma_n128_ss(O, dab + 2 * q, db + 128 * q, q ? 1 : first_acc);
            }
            wg_commit();
            g++;
        };
        auto issue_half = [&](float (&A)[64], uint32_t pg, uint32_t a_off) {
            const uint64_t da = make_desc(pg + a_off, 16), db = make_desc(pg + 2 * PAGE, 8192);
#pragma unroll
            for (int q = 0; q < 4; q++) wgmma_n128_ss(A, da + 2 * q, db + 128 * q, 1);
            wg_commit();
        };
        issue_q(0);
#pragma unroll 1
        for (int kb = 1; kb < DM / 64; kb++) {
            if (kb == DM / 64 - 3 && w == 1) bar_sync(4, 256);
            const bool defer = kb >= DM / 64 - 2;
            if (!defer) {
                issue_q(1);
            } else {
                wait_full(g);
                wg_fence();
                issue_half(S, sb + (g & 3) * (3 * PAGE), w * 8192);
                g++;
            }
            if (kb == DM / 64 - 2 && w == 0) bar_arrive(4, 256);
            wg_wait<1>();
            if (kb < DM / 64 - 1) release(g - 2);
            if (kb <= 8) {
                write_part(kb - 1);
                if (kb == 8) mark_done();
            }
        }
        uint32_t Q[32], Pm[32];
#pragma unroll
        for (int i = 0; i < 32; i++) Pm[i] = 0;
        float lim = (float)(v * 16 + (lane >> 2) - 8 * (lane & 3));
        l[0] = l[1] = 0.f;
        float mc[2] = {0.f, 0.f}, scale[2] = {0.f, 0.f}, sum[4];
        uint32_t kq = g * 8, vq = g * 8, ks = 0, vs = 0, ctl;
        int t = 0;
        reg_fence(Pm);
        asm volatile("" : "+f"(lim), "+f"(mc[0]), "+f"(mc[1]), "+f"(l[0]), "+f"(l[1]), "+f"(scale[0]), "+f"(scale[1]));
        asm volatile("" : "+r"(kq), "+r"(vq), "+r"(ks), "+r"(vs), "+r"(t));
        wg_wait<0>();
        reg_fence(S);
        reg_fence(O);
        PROF(2 + 2 * item, w);
        if (w == 0) PROF_GT(2 + 2 * item);

#pragma unroll
        for (int i = 0; i < 32; i++) Q[i] = pack_bf16(S[2 * i], S[2 * i + 1]);
        const uint32_t qpark = stg + lane * 16;
        constexpr int T = 17;
        uint32_t shifted = 0;
        uint32_t tick = 0;
        constexpr uint32_t SLOT = (2 * PAGE) >> 4;
        const uint32_t kdesc0 = (uint32_t)make_desc(sb, PAGE), vdesc0 = (uint32_t)make_desc(sb, 16);
        wait_full(g);
        do {
            bar_sync(2 + w, 256);
            wg_fence();
            issue_qk(S, Q, desc_hi | (kdesc0 + ks));
            wg_commit();
            ctl = __shfl_sync(~0u, ctl_tab, t);
            mbar_wait(sb + BAR_FULL + (vq & 56), (vq >> 6) & 1);
            uint32_t krel = empty_rel + (kq & 56), vrel = empty_rel + (vq & 56);
            const uint64_t vdesc = desc_hi | (vdesc0 + vs);
            if (ctl & CTL_SWITCH) {
                scale[0] = rcp_approx(quad_sum(l[0]));
                scale[1] = rcp_approx(quad_sum(l[1]));
                l[0] = l[1] = mc[0] = mc[1] = 0.f;
                shifted = false;
                pend = ptr_off(ctx_dst(item == 5, 0), chunk0);
                asm volatile("" : "+l"(pend));
                if (w == 1) { release((kq >> 3) - 2); release((kq >> 3) + 1); }
            }
            const uint32_t kadv = (ctl >> 16) & 7, vadv = ctl >> 20;
            kq += kadv * 8; ks += kadv * SLOT; ks = ks >= 6 * SLOT ? ks - 6 * SLOT : ks;
            vq += vadv * 8; vs += vadv * SLOT; vs = vs >= 6 * SLOT ? vs - 6 * SLOT : vs;
            t++;
            uint32_t kbar = sb + BAR_FULL + (kq & 56), kpar = (kq >> 6) & 1;
            asm volatile("" : "+r"(krel), "+r"(vrel), "+r"(kbar), "+r"(kpar), "+r"(ks), "+r"(vs), "+r"(kq), "+r"(vq), "+r"(t));
            if (!(ctl & (CTL_START | CTL_PVHALF))) {
                wg_fence();
                issue_pv<0, 1>(O, Pm, vdesc, ctl & CTL_PVACC);
                wg_commit();
                issue_pv<1, 4>(O, Pm, vdesc, 1);
                wg_commit();
                issue_pv<4, 8>(O, Pm, vdesc, 1);
                wg_commit();
            } else if (ctl & CTL_PVHALF) {
                wg_fence();
                issue_pv<0, 1>(O, Pm, vdesc, ctl & CTL_PVACC);
                wg_commit();
                issue_pv<1, 4>(O, Pm, vdesc, 1);
                wg_commit();
                wg_commit();
            } else {
                wg_fence();
                issue_half(O, sb + 6 * PAGE, PAGE + (1 - w) * 8192);
                issue_half(O, sb + 9 * PAGE, PAGE + (1 - w) * 8192);
            }
            bar_arrive(3 - w, 256);
            auto scores_done = [&]() {
                sched_fence(tick, lane < 3);
                wg_wait<2>();
                reg_fence(S);
                if (lane < 3) mbar_arrive_cluster(krel);
            };
            auto load_q = [&]() {
#pragma unroll
                for (int i = 0; i < 8; i++) lds128(qpark + (i >> 2) * 8192 + (i & 3) * 512, Q[4 * i], Q[4 * i + 1], Q[4 * i + 2], Q[4 * i + 3]);
            };
            if ((ctl & (CTL_HALF | CTL_MASKHI)) || shifted) {
                scores_done();
                if (ctl & CTL_LOADQ) load_q();
                if (ctl & CTL_HALF) mask_half<0>(S, lim);
                if (ctl & CTL_MASKHI) mask_half<8>(S, lim);
                if (shifted) shift_rows(S, mc[0], mc[1]);
            } else {
                scores_done();
            }
            const bool kready = mbar_test(kbar, kpar);
            sum[0] = sum[1] = sum[2] = sum[3] = 0.f;
            float e[64];
#pragma unroll
            for (int i = 0; i < 16; i++) asm volatile("" : "+r"(Pm[i])::"memory");
            exp_stages<0, 16, 32, 4 + LAG>(S, e, Pm, sum, tick, lane < 3);
            auto pv_done = [&](bool rel) {
                sched_fence(tick, lane < 3);
                wg_wait<0>();
                reg_fence(O);
                if (rel && lane < 3) mbar_arrive_cluster(vrel);
#pragma unroll
                for (int i = 16; i < 32; i++) asm volatile("" : "+r"(Pm[i])::"memory");
            };
            const bool half = ctl & CTL_HALF, first = ctl & (CTL_START | CTL_SWITCH);
            float limit = SUM_HI;
            float a0 = 0.f, a1 = 0.f, ta = 0.f, tb = 0.f;
            auto low_check = [&](int k) {
                auto bfly = [](float x, int m) { float r; asm volatile("shfl.sync.bfly.b32 %0, %1, %2, 0x1f, 0xffffffff;" : "=f"(r) : "f"(x), "r"(m)); return r; };
                if (k == 16 + LAG) { a0 = sum[0] + sum[1]; a1 = sum[2] + sum[3]; asm volatile("" : "+f"(a0), "+f"(a1)); }
                if (k == 17 + LAG) { ta = bfly(a0, 1); tb = bfly(a1, 1); }
                if (k == 20 + LAG) { a0 += ta; a1 += tb; asm volatile("" : "+f"(a0), "+f"(a1)); }
                if (k == 21 + LAG) { ta = bfly(a0, 2); tb = bfly(a1, 2); }
                if (k == 24 + LAG) { if (!(fminf(a0 + ta, a1 + tb) >= SUM_LO)) limit = -1.f; asm volatile("" : "+f"(limit)); }
            };
            if (!(ctl & (CTL_HALF | CTL_SWITCH | CTL_START))) {
                pv_done(true);
                exp_stages<16, 32 + LAG, 32, -1>(S, e, Pm, sum, tick, lane < 3);
            } else if (half) {
                pv_done(!(ctl & CTL_START));
                exp_stages<16, 16 + LAG, 16, -1>(S, e, Pm, sum, tick, lane < 3);
                if (ctl & CTL_START) {
                    release(g - 2); release(g - 1);
#pragma unroll
                    for (int i = 0; i < 32; i++) Q[i] = pack_bf16(O[2 * i], O[2 * i + 1]);
                    if (!(fminf(quad_sum(sum[0] + sum[1]), quad_sum(sum[2] + sum[3])) >= SUM_LO)) limit = -1.f;
                }
            } else if (ctl & CTL_START) {
                pv_done(false);
                release(g - 2); release(g - 1);
                if (ctl & CTL_DIRECT) {
                    exp_stages<16, 32 + LAG, 32, -1>(S, e, Pm, sum, tick, lane < 3, [&](int k) {
                        low_check(k);
                        if (k < 32) {
#pragma unroll
                            for (int i = 2 * (k - 16); i < 2 * (k - 16) + 2; i++)
                                asm volatile("cvt.rn.bf16x2.f32 %0, %1, %2;" : "=r"(Q[i]) : "f"(O[2 * i + 1]), "f"(O[2 * i]));
                        }
                    });
                } else {
                    uint32_t u[32] = {};
                    exp_stages<16, 32 + LAG, 32, -1>(S, e, Pm, sum, tick, lane < 3, [&](int k) {
                        low_check(k);
                        if (k < 32) {
#pragma unroll
                            for (int i = 2 * (k - 16); i < 2 * (k - 16) + 2; i++)
                                asm volatile("cvt.rn.bf16x2.f32 %0, %1, %2;" : "=r"(u[i]) : "f"(O[2 * i + 1]), "f"(O[2 * i]));
                        }
                        const int i = (k - 18) >> 1;
                        if (k >= 18 && !(k & 1) && i < 8) sts128(qpark + (i >> 2) * 8192 + (i & 3) * 512, u[4 * i], u[4 * i + 1], u[4 * i + 2], u[4 * i + 3]);
                    });
                }
            } else {
                pv_done(true);
                uint8_t* d[2] = {pend, (uint8_t*)((uintptr_t)pend ^ 64)};
                uint32_t po[32] = {};
                exp_stages<16, 32 + LAG, 32, -1>(S, e, Pm, sum, tick, lane < 3, [&](int k) {
                    low_check(k);
                    const int q = (k - 18) >> 1;
                    if (k >= 19 && (k & 1) && q < 8)
                        __stcg(reinterpret_cast<uint4*>(d[(q >> 1) & 1] + (q >> 2) * PAGE + (q & 1) * 1024), make_uint4(po[4 * q], po[4 * q + 1], po[4 * q + 2], po[4 * q + 3]));
                    if (k >= 32) return;
                    const int i = (k - 16) >> 1, h = (k & 1) * 2;
                    const float sc = scale[i & 1];
#pragma unroll
                    for (int r = h; r < h + 2; r++) {
                        float x0, x1;
                        asm volatile("mul.f32 %0, %1, %2;" : "=f"(x0) : "f"(O[chunk_src(4 * i + r)]), "f"(sc));
                        asm volatile("mul.f32 %0, %1, %2;" : "=f"(x1) : "f"(O[chunk_src(4 * i + r) + 1]), "f"(sc));
                        asm volatile("cvt.rn.bf16x2.f32 %0, %1, %2;" : "=r"(po[4 * i + r]) : "f"(x1), "f"(x0));
                    }
                });
                mark_done();
            }
            sum[0] += sum[1]; sum[2] += sum[3];
            float chk = sum[0] + sum[2];
            const bool bad = !(chk <= limit);
            if (__any_sync(~0u, bad)) {
                if (half) {
#pragma unroll
                    for (int i = 32; i < 64; i++) S[i] = -INFINITY;
                }
                float d0 = fmaxf(S[0], S[1]), d1 = fmaxf(S[2], S[3]);
#pragma unroll
                for (int j = 1; j < 16; j++) {
                    d0 = fmaxf(d0, fmaxf(S[4 * j], S[4 * j + 1]));
                    d1 = fmaxf(d1, fmaxf(S[4 * j + 2], S[4 * j + 3]));
                }
                d0 = fmaxf(d0, __shfl_xor_sync(~0u, d0, 1));
                d1 = fmaxf(d1, __shfl_xor_sync(~0u, d1, 1));
                d0 = fmaxf(d0, __shfl_xor_sync(~0u, d0, 2));
                d1 = fmaxf(d1, __shfl_xor_sync(~0u, d1, 2));
                if (!first) {
                    d0 = fmaxf(d0, 0.f);
                    d1 = fmaxf(d1, 0.f);
                    const float a0 = ex2(-d0), a1 = ex2(-d1);
#pragma unroll
                    for (int j = 0; j < 16; j++) {
                        O[4 * j] *= a0; O[4 * j + 1] *= a0; O[4 * j + 2] *= a1; O[4 * j + 3] *= a1;
                    }
                    l[0] *= a0; l[1] *= a1;
                }
                mc[0] += d0; mc[1] += d1;
                shifted = true;
                shift_rows(S, d0, d1);
                sum[0] = sum[1] = sum[2] = sum[3] = 0.f;
                exp_part<0, 8>(S, Pm, sum);
                exp_part<8, 16>(S, Pm, sum);
                sum[0] += sum[1]; sum[2] += sum[3];
            }
            l[0] += sum[0]; l[1] += sum[2];
            if (!kready) mbar_wait(kbar, kpar);
        } while (t < T);
        asm volatile("" : "+r"(t));
        g += 36;
        if (t > T) asm volatile("st.shared.u32 [%0], %1;" ::"r"(sb + SM_PROF), "r"(tick) : "memory");
        if (w == 0) release(g - 3);
        const uint64_t vdesc = desc_hi | (vdesc0 + vs);
        wait_full(vq >> 3);
        if (ctl & CTL_HALF) {
            wg_fence();
            issue_pv<0, 4>(O, Pm, vdesc, !(ctl & CTL_SWITCH));
            wg_commit();
        } else {
            wg_fence();
            issue_pv<0, 4>(O, Pm, vdesc, !(ctl & CTL_SWITCH));
            issue_pv<4, 8>(O, Pm, vdesc, 1);
            wg_commit();
        }
        if (item == 5) break;
        finish_attention(0, g);
        PROF(3 + 2 * item, w);
        if (w == 0) PROF_GT(3 + 2 * item);
    }

    float acc[64];
    uint32_t slot = 0;
    const uint32_t da0 = (uint32_t)make_desc(sb + w * 8192, 16), db0 = (uint32_t)make_desc(sb + PAGE, 8192);
    uint32_t da = da0, db = db0, fbar = sb + BAR_FULL + (g & 7) * 8, fpar = (g >> 3) & 1, rel = 0;
    auto issue_out = [&](int first_acc) {
        mbar_wait(fbar, fpar);
        wg_fence();
#pragma unroll
        for (int q = 0; q < 4; q++) wgmma_n128_ss(acc, (desc_hi | da) + 2 * q, (desc_hi | db) + 128 * q, q ? 1 : first_acc);
        wg_commit();
        rel = empty_rel + ((g - 1) & 7) * 8;
        g++;
        slot = slot == SM_REGION - 2 * PAGE ? 0 : slot + 2 * PAGE;
        da = da0 + (slot >> 4); db = db0 + (slot >> 4);
        fbar = sb + BAR_FULL + (g & 7) * 8; fpar = (g >> 3) & 1;
        asm volatile("" : "+r"(da), "+r"(db), "+r"(fbar), "+r"(fpar), "+r"(rel), "+r"(slot), "+r"(g));
    };
    issue_out(0);
    finish_attention(1, g - 1);
    PROF(13, w);
    if (w == 0) PROF_GT(13);
    uint32_t xr[32], gr[32];
#pragma unroll
    for (int i = 0; i < 32; i++) gr[i] = 0;
#pragma unroll 1
    for (int kb = 1; kb < 64; kb++) {
        if (kb == 60 && w == 1) bar_sync(4, 256);
        issue_out(1);
        if (kb == 63 && w == 0) bar_arrive(4, 256);
        wg_wait<1>();
        if (kb < 60 && lane < 3) mbar_arrive_cluster(rel);
        if (kb <= 8 && !(kb & 1)) {
            store_part4(pend, (kb >> 1) - 1, pk);
            if (kb == 8) mark_done();
        }
        if (kb >= 28 && kb < 60 && (kb & 3) == 2 * w) {
            uint32_t u0, u1, u2, u3;
            const int s = (kb - 28) >> 2;
            mbar_wait(sb + BAR_G + w * 8, 0);
            ldmatrix_x4(slab_addr(stg, lane, s), u0, u1, u2, u3);
            set_quad(gr, s, pack_bf16(silu_f(bf_lo(u0)), silu_f(bf_hi(u0))), pack_bf16(silu_f(bf_lo(u1)), silu_f(bf_hi(u1))),
                     pack_bf16(silu_f(bf_lo(u2)), silu_f(bf_hi(u2))), pack_bf16(silu_f(bf_lo(u3)), silu_f(bf_hi(u3))));
        }
    }
    mbar_wait(fbar, fpar);
    const uint32_t xs = sb + slot + w * PAGE + v * 2048;
#pragma unroll
    for (int s = 0; s < 8; s++) ldmatrix_x4(slab_addr(xs, lane, s), xr[4 * s], xr[4 * s + 1], xr[4 * s + 2], xr[4 * s + 3]);
    wg_wait<0>();
    reg_fence(acc);
    PROF(14, w);
    if (w == 0) PROF_GT(14);
#pragma unroll
    for (int s = 0; s < 8; s++) {
        uint32_t o[4];
#pragma unroll
        for (int k = 0; k < 4; k++)
            o[k] = bf2_add(xr[4 * s + k], bf2_mul(pack_bf16(acc[8 * s + 2 * k], acc[8 * s + 2 * k + 1]), gr[4 * s + k]));
        stmatrix_x4(slab_addr(stg, lane, s), o[0], o[1], o[2], o[3]);
        if ((s & 3) == 3) {
            fence_async_smem();
            __syncwarp();
            const int orow = ((pair >> 1) & 7) * 256 + c * 128 + w * 64 + v * 16, ocol = (pair >> 4) * 256 + (pair & 1) * 128;
            if (lane == 0) tma_store_2d(m_out, ocol + (s >> 2) * 64, orow, stg + (s >> 2) * 8192);
        }
    }
    PROF(28, w);
    if (lane == 0) {
        bulk_commit();
        bulk_wait_read();
    }
    __syncwarp();
}

__global__ void __cluster_dims__(2, 1, 1) __launch_bounds__(384, 1)
fused_kernel(const __grid_constant__ CUtensorMap m_ckv, const __grid_constant__ CUtensorMap m_wuk,
             const __grid_constant__ CUtensorMap m_wuv, const __grid_constant__ CUtensorMap m_wq,
             const __grid_constant__ CUtensorMap m_wo, const __grid_constant__ CUtensorMap m_x,
             const __grid_constant__ CUtensorMap m_out, const __grid_constant__ CUtensorMap m_gate,
             const __grid_constant__ CUtensorMap m_up, const __grid_constant__ CUtensorMap m_down, const Params P) {
    extern __shared__ __align__(1024) uint8_t smem[];
    const uint32_t sb = __shfl_sync(~0u, smem_u32(smem), 0);
    const int tid = threadIdx.x;
    const int cl = blockIdx.x >> 1, c = blockIdx.x & 1;
    const int pair = cl >= 64 ? cl : cl < 4 ? cl * 16 + 15 : cl < 36 ? ((cl - 4) >> 3) * 16 + ((cl - 4) & 7)
                                                                    : ((cl - 36) / 7) * 16 + 8 + (cl - 36) % 7;
    const int warp = __shfl_sync(~0u, tid >> 5, 0), lane = tid & 31;
    auto init_barriers = [&](int i0, int i1) {
#pragma unroll
        for (int i = i0; i < i1; i++) mbar_init(sb + SM_BAR + i * 8, (i >> 3) == 1 ? 16 : i >= 25 ? 8 : 1);
        asm volatile("fence.mbarrier_init.release.cluster;" ::: "memory");
    };
    auto finish = [&]() {
        PROF(29, tid >> 7);
        if (tid == 0) atomicAdd(&g_sync.done, 1u);
    };
    if (pair >= NMAIN / 2) {
        if (tid == 256) init_barriers(0, 16);
        if (tid == 288) *reinterpret_cast<uint32_t*>(smem + PAUSE) = 0;
        __syncthreads();
        const unsigned epoch = __ldcg(&g_sync.done) / NCTA;
        if (warp < 8) ffn_cta(smem, sb, blockIdx.x - NMAIN, epoch, P.w_r);
        else if (tid == 256) ffn_producer(sb, blockIdx.x - NMAIN, epoch + 1, &m_gate, &m_up, &m_down);
        else if (tid == 288) ffn_pacer(sb, epoch + 1);
        __syncwarp();
        finish();
    } else if (warp < 8) {
        const uint32_t r0 = tid >> 3, ch = tid & 7, dst = sb + r0 * 128 + ((ch ^ (r0 & 7)) << 4);
        const uint32_t wo = r0 * 8192 + (pair & 15) * 256 + c * 128 + ch * 16;
        const uint8_t* sw[2] = {ptr_off(P.w_uk, wo), ptr_off(P.w_uv, wo)};
        const uint8_t* sc = ptr_off(P.c_kv, ((pair >> 4) * 512 + r0) * 1024 + ch * 16);
#pragma unroll
        for (int i = 0; i < 4; i++) cp_async16(dst + i * 4096, sw[i >> 1] + (i & 1) * 262144);
#pragma unroll
        for (int i = 0; i < 8; i++) cp_async16(dst + PAGE + i * 4096, sc + i * 32768);
        asm volatile("barrier.cluster.arrive.relaxed.aligned;" ::: "memory");
        asm volatile("setmaxnreg.inc.sync.aligned.u32 240;");
        consumer(sb, pair, c, &m_out, (const uint8_t*)P.x);
        finish();
    } else {
        asm volatile("setmaxnreg.dec.sync.aligned.u32 24;");
        auto load_w = [&](int kb) {
            tma_3d(sb + kb * (3 * PAGE), &m_wuk, 0, kb * 64, (pair & 15) * 2 + c, sb + BAR_FULL + kb * 8);
            tma_3d(sb + kb * (3 * PAGE) + 8192, &m_wuv, 0, kb * 64, (pair & 15) * 2 + c, sb + BAR_FULL + kb * 8);
        };
        if (tid == 256) {
            init_barriers(0, NBAR);
            prefetch_map(&m_ckv);
            prefetch_map(&m_wuv);
            mbar_arrive(sb + BAR_FULL);
#pragma unroll 1
            for (int kb = 1; kb < 4; kb++) {
                mbar_expect_tx(sb + BAR_FULL + kb * 8, 3 * PAGE);
                if (kb <= 1) load_w(kb);
            }
        }
        PROF(18, 0);
        __syncwarp();
        cluster_sync();
        PROF(22, 0);
        if (tid == 256) {
#pragma unroll 1
            for (int kb = 1; kb < 4; kb++) {
                if (kb > 1) load_w(kb);
                tma_3d_mc(sb + kb * (3 * PAGE) + (1 + c) * PAGE, &m_ckv, 0, (pair >> 4) * 512 + c * 128, kb, sb + BAR_FULL + kb * 8);
            }
        }
        __syncwarp();
        PROF(19, 0);
        if (warp == 10) {
            sync_helper(sb, lane, pair, c);
        } else if (warp & 1) {
            fetch_helper(P.c_kv, sb, (warp >> 1) & 1, lane, pair, c);
        } else {
            producer(P, sb, pair, c, &m_ckv, &m_wuk, &m_wuv, &m_wq, &m_wo, &m_x, &m_out);
        }
    }
}

typedef CUresult (*EncodeFn)(CUtensorMap*, CUtensorMapDataType, cuuint32_t, void*, const cuuint64_t*, const cuuint64_t*,
                             const cuuint32_t*, const cuuint32_t*, CUtensorMapInterleave, CUtensorMapSwizzle,
                             CUtensorMapL2promotion, CUtensorMapFloatOOBfill);

void make_map_2d(EncodeFn fn, CUtensorMap* m, const void* ptr, int rows, int cols, int box_rows) {
    cuuint64_t dims[2] = {(cuuint64_t)cols, (cuuint64_t)rows};
    cuuint64_t strides[1] = {(cuuint64_t)cols * 2};
    cuuint32_t box[2] = {64, (cuuint32_t)box_rows};
    cuuint32_t es[2] = {1, 1};
    fn(m, CU_TENSOR_MAP_DATA_TYPE_BFLOAT16, 2, const_cast<void*>(ptr), dims, strides, box, es, CU_TENSOR_MAP_INTERLEAVE_NONE,
       CU_TENSOR_MAP_SWIZZLE_128B, CU_TENSOR_MAP_L2_PROMOTION_L2_256B, CU_TENSOR_MAP_FLOAT_OOB_FILL_NONE);
}
void make_map_w(EncodeFn fn, CUtensorMap* m, const void* ptr, int rows, int cols, int blocks, int box_rows) {
    cuuint64_t dims[3] = {64, (cuuint64_t)rows, (cuuint64_t)cols / 64};
    cuuint64_t strides[2] = {(cuuint64_t)cols * 2, 128};
    cuuint32_t box[3] = {64, (cuuint32_t)box_rows, (cuuint32_t)blocks};
    cuuint32_t es[3] = {1, 1, 1};
    fn(m, CU_TENSOR_MAP_DATA_TYPE_BFLOAT16, 3, const_cast<void*>(ptr), dims, strides, box, es, CU_TENSOR_MAP_INTERLEAVE_NONE,
       CU_TENSOR_MAP_SWIZZLE_128B, CU_TENSOR_MAP_L2_PROMOTION_L2_128B, CU_TENSOR_MAP_FLOAT_OOB_FILL_NONE);
}

void make_map_wo(EncodeFn fn, CUtensorMap* m, const void* ptr) {
    cuuint64_t dims[5] = {DM, 2, 4, 4, NH * 128 / 32};
    cuuint64_t strides[4] = {DM * 2, 8 * DM * 2, 2 * DM * 2, 32 * DM * 2};
    cuuint32_t box[5] = {64, 2, 4, 4, 2};
    cuuint32_t es[5] = {1, 1, 1, 1, 1};
    fn(m, CU_TENSOR_MAP_DATA_TYPE_BFLOAT16, 5, const_cast<void*>(ptr), dims, strides, box, es, CU_TENSOR_MAP_INTERLEAVE_NONE,
       CU_TENSOR_MAP_SWIZZLE_128B, CU_TENSOR_MAP_L2_PROMOTION_L2_256B, CU_TENSOR_MAP_FLOAT_OOB_FILL_NONE);
}

}

extern "C" void kernel_launch(void* const* d_in, const int* in_sizes, int n_in, void* d_out, int out_size) {
    static EncodeFn fn = nullptr;
    if (!fn) {
        void* f = nullptr;
        cudaDriverEntryPointQueryResult qr;
        cudaGetDriverEntryPoint("cuTensorMapEncodeTiled", &f, cudaEnableDefault, &qr);
        fn = (EncodeFn)f;
        cudaFuncSetAttribute(fused_kernel, cudaFuncAttributeMaxDynamicSharedMemorySize, SMEM_BYTES);
    }
    CUtensorMap m_ckv, m_wuk, m_wuv, m_wq, m_wo, m_x, m_out, m_gate, m_up, m_down;
    make_map_w(fn, &m_gate, d_in[8], DM, FF, FS / 64, 16);
    make_map_w(fn, &m_up, d_in[9], DM, FF, FS / 64, 16);
    make_map_w(fn, &m_down, d_in[10], FF, DM, DM / 64, 16);
    make_map_w(fn, &m_ckv, d_in[1], SEQ, DC, 1, 128);
    make_map_w(fn, &m_wq, d_in[2], DM, NH * 128, 1, 64);
    make_map_w(fn, &m_wuk, d_in[3], DC, NH * 128, 1, 64);
    make_map_w(fn, &m_wuv, d_in[4], DC, NH * 128, 1, 64);
    make_map_wo(fn, &m_wo, d_in[5]);
    make_map_w(fn, &m_x, d_in[0], SEQ, DM, 2, 64);
    make_map_2d(fn, &m_out, d_out, SEQ, DM, 16);
    Params P;
    P.x = (const __nv_bfloat16*)d_in[0];
    P.w_r = (const __nv_bfloat16*)d_in[7];
    P.c_kv = (const uint8_t*)d_in[1];
    P.w_uk = (const uint8_t*)d_in[3];
    P.w_uv = (const uint8_t*)d_in[4];
    P.w_o = (const uint8_t*)d_in[5];
    fused_kernel<<<NCTA, 384, SMEM_BYTES>>>(m_ckv, m_wuk, m_wuv, m_wq, m_wo, m_x, m_out, m_gate, m_up, m_down, P);
}
```

```cpp
#include <cuda_runtime.h>
#include <cuda_bf16.h>
#include <cuda.h>
#include <stdint.h>

namespace {

constexpr int SEQ = 2048, DM = 1024, NH = 32, DC = 512, FF = 3584;
constexpr int PAGE = 16384;
constexpr int NRING = 12;
constexpr int NCTA = 132, NMAIN = 128;
constexpr uint32_t SM_REGION = NRING * PAGE;
constexpr uint32_t SM_BAR = (NRING + 2) * PAGE;
constexpr uint32_t BAR_FULL = SM_BAR, BAR_EMPTY = SM_BAR + 64;
constexpr uint32_t BAR_DEP = SM_BAR + 128;
constexpr uint32_t BAR_G = SM_BAR + 184;
constexpr uint32_t BAR_DONE = SM_BAR + 200;
constexpr uint32_t BAR_EMPTYL = SM_BAR + 216;
constexpr int NBAR = 35;
constexpr uint32_t SM_PROF = SM_BAR + 320;
constexpr int SMEM_BYTES = SM_PROF + 512;
constexpr uint32_t SPIN_LIMIT = 1u << 16;
constexpr uint32_t POLL_MASK = 7;

struct SyncBlock {
    unsigned done;       unsigned pad0[31];
    unsigned ln;         unsigned pad1[31];
    unsigned router;     unsigned pad4[31];
    unsigned ffn_ticket; unsigned pad2[31];
    unsigned ffn_done;   unsigned pad3[31];
    unsigned kv[NH * 8];
    unsigned kvfree[16 * 8];
    unsigned ctx[32 * NH];
};

__device__ __align__(1024) uint8_t g_xn[8 * 16 * 4 * 8192];
__device__ __align__(1024) uint8_t g_kv[16 * 16 * 65536];
__device__ __align__(1024) uint8_t g_ctx[16 * 64 * 16384];
__device__ __align__(16) uint4 g_routed[2 * 128];
__device__ int g_sel[2];
__device__ __align__(16) float g_r[SEQ];
__device__ __align__(16) float g_ypart[4 * 2 * DM];
__device__ SyncBlock g_sync;

__device__ __forceinline__ uint32_t smem_u32(const void* p) { return (uint32_t)__cvta_generic_to_shared(p); }

__device__ __forceinline__ void mbar_init(uint32_t bar, uint32_t count) {
    asm volatile("mbarrier.init.shared::cta.b64 [%0], %1;" ::"r"(bar), "r"(count) : "memory");
}
#define MBAR_WAIT_ASM(HINT, LIMIT)                                                                  \
    asm volatile("{\n.reg .pred p;\n.reg .u32 n;\nmov.u32 n, 0;\n"                                  \
                 "WAIT_LOOP:\n"                                                                     \
                 "mbarrier.try_wait.parity.shared::cta.b64 p, [%0], %1" HINT ";\n"                  \
                 "@p bra WAIT_DONE;\n"                                                              \
                 "add.u32 n, n, 1;\n"                                                               \
                 "setp.lt.u32 p, n, " LIMIT ";\n"                                                   \
                 "@p bra WAIT_LOOP;\n"                                                              \
                 "WAIT_DONE:\n}\n" ::"r"(bar), "r"(parity) : "memory")
__device__ __forceinline__ void mbar_wait(uint32_t bar, uint32_t parity) { MBAR_WAIT_ASM("", "131072"); }
__device__ __forceinline__ void mbar_sleep(uint32_t bar, uint32_t parity) { MBAR_WAIT_ASM(", 2000", "8192"); }
__device__ __forceinline__ bool mbar_try(uint32_t bar, uint32_t parity) {
    uint32_t ok;
    asm volatile("{\n.reg .pred p;\nmbarrier.try_wait.parity.shared::cta.b64 p, [%1], %2;\nselp.u32 %0, 1, 0, p;\n}\n"
                 : "=r"(ok) : "r"(bar), "r"(parity) : "memory");
    return ok;
}
__device__ __forceinline__ bool mbar_test(uint32_t bar, uint32_t parity) {
    uint32_t ok;
    asm volatile("{\n.reg .pred p;\nmbarrier.test_wait.parity.shared::cta.b64 p, [%1], %2;\nselp.u32 %0, 1, 0, p;\n}\n"
                 : "=r"(ok) : "r"(bar), "r"(parity) : "memory");
    return ok;
}
__device__ __forceinline__ bool elect_one() {
    uint32_t ok;
    asm volatile("{\n.reg .pred p;\nelect.sync _|p, 0xffffffff;\nselp.u32 %0, 1, 0, p;\n}\n" : "=r"(ok));
    return ok;
}
__device__ __forceinline__ void mbar_arrive(uint32_t bar) {
    asm volatile("mbarrier.arrive.shared::cta.b64 _, [%0];" ::"r"(bar) : "memory");
}
__device__ __forceinline__ void mbar_expect_tx(uint32_t bar, uint32_t bytes) {
    asm volatile("mbarrier.arrive.expect_tx.shared::cta.b64 _, [%0], %1;" ::"r"(bar), "r"(bytes) : "memory");
}
__device__ __forceinline__ void mbar_arrive_cluster(uint32_t cluster_addr) {
    asm volatile("mbarrier.arrive.shared::cluster.b64 _, [%0];" ::"r"(cluster_addr) : "memory");
}
__device__ __forceinline__ uint32_t mapa(uint32_t addr, uint32_t rank) {
    uint32_t r;
    asm("mapa.shared::cluster.u32 %0, %1, %2;" : "=r"(r) : "r"(addr), "r"(rank));
    return r;
}
__device__ __forceinline__ void tma_3d(uint32_t dst, const CUtensorMap* m, int c0, int c1, int c2, uint32_t bar) {
    asm volatile("cp.async.bulk.tensor.3d.shared::cluster.global.mbarrier::complete_tx::bytes [%0], [%1, {%3, %4, %5}], [%2];"
                 ::"r"(dst), "l"(m), "r"(bar), "r"(c0), "r"(c1), "r"(c2) : "memory");
}
__device__ __forceinline__ void tma_3d_hint(uint32_t dst, const CUtensorMap* m, int c0, int c1, int c2, uint32_t bar, uint64_t pol) {
    asm volatile("cp.async.bulk.tensor.3d.shared::cluster.global.mbarrier::complete_tx::bytes.L2::cache_hint [%0], [%1, {%3, %4, %5}], [%2], %6;"
                 ::"r"(dst), "l"(m), "r"(bar), "r"(c0), "r"(c1), "r"(c2), "l"(pol) : "memory");
}
__device__ __forceinline__ void tma_3d_mc(uint32_t dst, const CUtensorMap* m, int c0, int c1, int c2, uint32_t bar) {
    asm volatile("cp.async.bulk.tensor.3d.shared::cluster.global.mbarrier::complete_tx::bytes.multicast::cluster [%0], [%1, {%3, %4, %5}], [%2], %6;"
                 ::"r"(dst), "l"(m), "r"(bar), "r"(c0), "r"(c1), "r"(c2), "h"((uint16_t)3) : "memory");
}
__device__ __forceinline__ void tma_5d_mc(uint32_t dst, const CUtensorMap* m, int c0, int c4, uint32_t bar) {
    asm volatile("cp.async.bulk.tensor.5d.shared::cluster.global.mbarrier::complete_tx::bytes.multicast::cluster [%0], [%1, {%3, 0, 0, 0, %4}], [%2], %5;"
                 ::"r"(dst), "l"(m), "r"(bar), "r"(c0), "r"(c4), "h"((uint16_t)3) : "memory");
}
__device__ __forceinline__ void bulk_load(uint32_t dst, const void* src, uint32_t bytes, uint32_t bar) {
    asm volatile("cp.async.bulk.shared::cluster.global.mbarrier::complete_tx::bytes [%0], [%1], %2, [%3];"
                 ::"r"(dst), "l"(src), "r"(bytes), "r"(bar) : "memory");
}
__device__ __forceinline__ void cp_async16(uint32_t dst, const void* src) {
    asm volatile("cp.async.cg.shared.global [%0], [%1], 16;" ::"r"(dst), "l"(src) : "memory");
}
__device__ __forceinline__ void bulk_load_mc(uint32_t dst, const void* src, uint32_t bytes, uint32_t bar) {
    asm volatile("cp.async.bulk.shared::cluster.global.mbarrier::complete_tx::bytes.multicast::cluster [%0], [%1], %2, [%3], %4;"
                 ::"r"(dst), "l"(src), "r"(bytes), "r"(bar), "h"((uint16_t)3) : "memory");
}
__device__ __forceinline__ void tma_store_2d(const CUtensorMap* m, int c0, int c1, uint32_t src) {
    asm volatile("cp.async.bulk.tensor.2d.global.shared::cta.bulk_group [%0, {%2, %3}], [%1];"
                 ::"l"(m), "r"(src), "r"(c0), "r"(c1) : "memory");
}
__device__ __forceinline__ void bulk_commit() { asm volatile("cp.async.bulk.commit_group;" ::: "memory"); }
__device__ __forceinline__ void bulk_wait_read() { asm volatile("cp.async.bulk.wait_group.read 0;" ::: "memory"); }
__device__ __forceinline__ void fence_async_smem() { asm volatile("fence.proxy.async.shared::cta;" ::: "memory"); }
__device__ __forceinline__ void prefetch_map(const CUtensorMap* m) {
    asm volatile("prefetch.tensormap [%0];" ::"l"(m) : "memory");
}
__device__ __forceinline__ void red_release(unsigned* p) {
    asm volatile("red.release.gpu.global.add.u32 [%0], 1;" ::"l"(p) : "memory");
}
__device__ __forceinline__ unsigned ld_relaxed(const unsigned* p) {
    unsigned v;
    asm volatile("ld.relaxed.gpu.global.u32 %0, [%1];" : "=r"(v) : "l"(p) : "memory");
    return v;
}
__device__ __forceinline__ void wait_counter(const unsigned* p, unsigned target, unsigned ns = 100) {
    for (uint32_t n = 0; (int)(ld_relaxed(p) - target) < 0 && n < SPIN_LIMIT; n++) __nanosleep(ns);
    asm volatile("fence.acquire.gpu;" ::: "memory");
    asm volatile("fence.proxy.async.global;" ::: "memory");
}
__device__ __forceinline__ void bar_sync(int id, int n) { asm volatile("bar.sync %0, %1;" ::"r"(id), "r"(n) : "memory"); }
__device__ __forceinline__ void bar_arrive(int id, int n) { asm volatile("bar.arrive %0, %1;" ::"r"(id), "r"(n) : "memory"); }
__device__ __forceinline__ void cluster_sync() {
    asm volatile("barrier.cluster.arrive.relaxed.aligned;\nbarrier.cluster.wait.aligned;" ::: "memory");
}
__device__ __forceinline__ void wg_fence() { asm volatile("wgmma.fence.sync.aligned;" ::: "memory"); }
__device__ __forceinline__ void wg_commit() { asm volatile("wgmma.commit_group.sync.aligned;" ::: "memory"); }
template <int N> __device__ __forceinline__ void wg_wait() { asm volatile("wgmma.wait_group.sync.aligned %0;" ::"n"(N) : "memory"); }
template <int N> __device__ __forceinline__ void reg_fence(float (&a)[N]) {
#pragma unroll
    for (int i = 0; i < N; i++) asm volatile("" : "+f"(a[i])::"memory");
}
template <int N> __device__ __forceinline__ void reg_fence(uint32_t (&a)[N]) {
#pragma unroll
    for (int i = 0; i < N; i++) asm volatile("" : "+r"(a[i])::"memory");
}
__device__ __forceinline__ uint32_t pack_bf16(float lo, float hi) {
    uint32_t r;
    asm("cvt.rn.bf16x2.f32 %0, %1, %2;" : "=r"(r) : "f"(hi), "f"(lo));
    return r;
}
__device__ __forceinline__ float bf_lo(uint32_t v) { return __uint_as_float(v << 16); }
__device__ __forceinline__ float bf_hi(uint32_t v) { return __uint_as_float(v & 0xffff0000u); }
__device__ __forceinline__ float bf_round(float v) { return __bfloat162float(__float2bfloat16_rn(v)); }
__device__ __forceinline__ float ex2(float v) {
    float r;
    asm("ex2.approx.ftz.f32 %0, %1;" : "=f"(r) : "f"(v));
    return r;
}
__device__ __forceinline__ float sqrt_approx(float v) {
    float r;
    asm("sqrt.approx.ftz.f32 %0, %1;" : "=f"(r) : "f"(v));
    return r;
}
__device__ __forceinline__ float rcp_approx(float v) {
    float r;
    asm("rcp.approx.ftz.f32 %0, %1;" : "=f"(r) : "f"(v));
    return r;
}
__device__ __forceinline__ float silu_f(float v) { return v * rcp_approx(1.0f + ex2(v * -1.4426950408889634f)); }
__device__ __forceinline__ void stmatrix_x4(uint32_t addr, uint32_t r0, uint32_t r1, uint32_t r2, uint32_t r3) {
    asm volatile("stmatrix.sync.aligned.m8n8.x4.shared.b16 [%0], {%1, %2, %3, %4};"
                 ::"r"(addr), "r"(r0), "r"(r1), "r"(r2), "r"(r3) : "memory");
}
__device__ __forceinline__ void sts128(uint32_t addr, uint32_t r0, uint32_t r1, uint32_t r2, uint32_t r3) {
    asm volatile("st.shared.v4.b32 [%0], {%1, %2, %3, %4};" ::"r"(addr), "r"(r0), "r"(r1), "r"(r2), "r"(r3) : "memory");
}
__device__ __forceinline__ void lds128(uint32_t addr, uint32_t& r0, uint32_t& r1, uint32_t& r2, uint32_t& r3) {
    asm volatile("ld.shared.v4.b32 {%0, %1, %2, %3}, [%4];" : "=r"(r0), "=r"(r1), "=r"(r2), "=r"(r3) : "r"(addr) : "memory");
}
__device__ __forceinline__ void ldmatrix_x4(uint32_t addr, uint32_t& r0, uint32_t& r1, uint32_t& r2, uint32_t& r3) {
    asm volatile("ldmatrix.sync.aligned.m8n8.x4.shared.b16 {%0, %1, %2, %3}, [%4];"
                 : "=r"(r0), "=r"(r1), "=r"(r2), "=r"(r3) : "r"(addr) : "memory");
}
__device__ __forceinline__ uint32_t bf2_mul(uint32_t a, uint32_t b) {
    uint32_t r;
    asm("mul.rn.bf16x2 %0, %1, %2;" : "=r"(r) : "r"(a), "r"(b));
    return r;
}
__device__ __forceinline__ uint32_t bf2_add(uint32_t a, uint32_t b) {
    uint32_t r;
    asm("add.rn.bf16x2 %0, %1, %2;" : "=r"(r) : "r"(a), "r"(b));
    return r;
}
__device__ __forceinline__ uint64_t policy_evict_first() {
    uint64_t p;
    asm("createpolicy.fractional.L2::evict_first.b64 %0, 1.0;" : "=l"(p));
    return p;
}

__device__ __forceinline__ uint64_t make_desc(uint32_t addr, uint32_t lbo_bytes) {
    return (uint64_t)((addr & 0x3FFFF) >> 4) | ((uint64_t)(lbo_bytes >> 4) << 16) | ((uint64_t)(1024 >> 4) << 32) | (1ull << 62);
}

__device__ __forceinline__ void wgmma_n256_ss(float (&d)[128], uint64_t da, uint64_t db, int acc) {
    asm volatile(
        "{\n.reg .pred p;\nsetp.ne.b32 p, %130, 0;\n"
        "wgmma.mma_async.sync.aligned.m64n256k16.f32.bf16.bf16 {"
        "%0, %1, %2, %3, %4, %5, %6, %7, %8, %9, %10, %11, %12, %13, %14, %15, "
        "%16, %17, %18, %19, %20, %21, %22, %23, %24, %25, %26, %27, %28, %29, %30, %31, "
        "%32, %33, %34, %35, %36, %37, %38, %39, %40, %41, %42, %43, %44, %45, %46, %47, "
        "%48, %49, %50, %51, %52, %53, %54, %55, %56, %57, %58, %59, %60, %61, %62, %63, "
        "%64, %65, %66, %67, %68, %69, %70, %71, %72, %73, %74, %75, %76, %77, %78, %79, "
        "%80, %81, %82, %83, %84, %85, %86, %87, %88, %89, %90, %91, %92, %93, %94, %95, "
        "%96, %97, %98, %99, %100, %101, %102, %103, %104, %105, %106, %107, %108, %109, %110, %111, "
        "%112, %113, %114, %115, %116, %117, %118, %119, %120, %121, %122, %123, %124, %125, %126, %127"
        "}, %128, %129, p, 1, 1, 1, 0;\n}\n"
        :
        "+f"(d[0]), "+f"(d[1]), "+f"(d[2]), "+f"(d[3]), "+f"(d[4]), "+f"(d[5]), "+f"(d[6]), "+f"(d[7]),
        "+f"(d[8]), "+f"(d[9]), "+f"(d[10]), "+f"(d[11]), "+f"(d[12]), "+f"(d[13]), "+f"(d[14]), "+f"(d[15]),
        "+f"(d[16]), "+f"(d[17]), "+f"(d[18]), "+f"(d[19]), "+f"(d[20]), "+f"(d[21]), "+f"(d[22]), "+f"(d[23]),
        "+f"(d[24]), "+f"(d[25]), "+f"(d[26]), "+f"(d[27]), "+f"(d[28]), "+f"(d[29]), "+f"(d[30]), "+f"(d[31]),
        "+f"(d[32]), "+f"(d[33]), "+f"(d[34]), "+f"(d[35]), "+f"(d[36]), "+f"(d[37]), "+f"(d[38]), "+f"(d[39]),
        "+f"(d[40]), "+f"(d[41]), "+f"(d[42]), "+f"(d[43]), "+f"(d[44]), "+f"(d[45]), "+f"(d[46]), "+f"(d[47]),
        "+f"(d[48]), "+f"(d[49]), "+f"(d[50]), "+f"(d[51]), "+f"(d[52]), "+f"(d[53]), "+f"(d[54]), "+f"(d[55]),
        "+f"(d[56]), "+f"(d[57]), "+f"(d[58]), "+f"(d[59]), "+f"(d[60]), "+f"(d[61]), "+f"(d[62]), "+f"(d[63]),
        "+f"(d[64]), "+f"(d[65]), "+f"(d[66]), "+f"(d[67]), "+f"(d[68]), "+f"(d[69]), "+f"(d[70]), "+f"(d[71]),
        "+f"(d[72]), "+f"(d[73]), "+f"(d[74]), "+f"(d[75]), "+f"(d[76]), "+f"(d[77]), "+f"(d[78]), "+f"(d[79]),
        "+f"(d[80]), "+f"(d[81]), "+f"(d[82]), "+f"(d[83]), "+f"(d[84]), "+f"(d[85]), "+f"(d[86]), "+f"(d[87]),
        "+f"(d[88]), "+f"(d[89]), "+f"(d[90]), "+f"(d[91]), "+f"(d[92]), "+f"(d[93]), "+f"(d[94]), "+f"(d[95]),
        "+f"(d[96]), "+f"(d[97]), "+f"(d[98]), "+f"(d[99]), "+f"(d[100]), "+f"(d[101]), "+f"(d[102]), "+f"(d[103]),
        "+f"(d[104]), "+f"(d[105]), "+f"(d[106]), "+f"(d[107]), "+f"(d[108]), "+f"(d[109]), "+f"(d[110]), "+f"(d[111]),
        "+f"(d[112]), "+f"(d[113]), "+f"(d[114]), "+f"(d[115]), "+f"(d[116]), "+f"(d[117]), "+f"(d[118]), "+f"(d[119]),
        "+f"(d[120]), "+f"(d[121]), "+f"(d[122]), "+f"(d[123]), "+f"(d[124]), "+f"(d[125]), "+f"(d[126]), "+f"(d[127])
        : "l"(da), "l"(db), "r"(acc));
}

template <int TB>
__device__ __forceinline__ void wgmma_n128_rs(float (&d)[64], uint32_t a0, uint32_t a1, uint32_t a2, uint32_t a3, uint64_t db, int acc) {
    asm volatile(
        "{\n.reg .pred p;\nsetp.ne.b32 p, %69, 0;\n"
        "wgmma.mma_async.sync.aligned.m64n128k16.f32.bf16.bf16 {"
        "%0, %1, %2, %3, %4, %5, %6, %7, %8, %9, %10, %11, %12, %13, %14, %15, "
        "%16, %17, %18, %19, %20, %21, %22, %23, %24, %25, %26, %27, %28, %29, %30, %31, "
        "%32, %33, %34, %35, %36, %37, %38, %39, %40, %41, %42, %43, %44, %45, %46, %47, "
        "%48, %49, %50, %51, %52, %53, %54, %55, %56, %57, %58, %59, %60, %61, %62, %63"
        "}, {%64, %65, %66, %67}, %68, p, 1, 1, %70;\n}\n"
        :
        "+f"(d[0]), "+f"(d[1]), "+f"(d[2]), "+f"(d[3]), "+f"(d[4]), "+f"(d[5]), "+f"(d[6]), "+f"(d[7]),
        "+f"(d[8]), "+f"(d[9]), "+f"(d[10]), "+f"(d[11]), "+f"(d[12]), "+f"(d[13]), "+f"(d[14]), "+f"(d[15]),
        "+f"(d[16]), "+f"(d[17]), "+f"(d[18]), "+f"(d[19]), "+f"(d[20]), "+f"(d[21]), "+f"(d[22]), "+f"(d[23]),
        "+f"(d[24]), "+f"(d[25]), "+f"(d[26]), "+f"(d[27]), "+f"(d[28]), "+f"(d[29]), "+f"(d[30]), "+f"(d[31]),
        "+f"(d[32]), "+f"(d[33]), "+f"(d[34]), "+f"(d[35]), "+f"(d[36]), "+f"(d[37]), "+f"(d[38]), "+f"(d[39]),
        "+f"(d[40]), "+f"(d[41]), "+f"(d[42]), "+f"(d[43]), "+f"(d[44]), "+f"(d[45]), "+f"(d[46]), "+f"(d[47]),
        "+f"(d[48]), "+f"(d[49]), "+f"(d[50]), "+f"(d[51]), "+f"(d[52]), "+f"(d[53]), "+f"(d[54]), "+f"(d[55]),
        "+f"(d[56]), "+f"(d[57]), "+f"(d[58]), "+f"(d[59]), "+f"(d[60]), "+f"(d[61]), "+f"(d[62]), "+f"(d[63])
        : "r"(a0), "r"(a1), "r"(a2), "r"(a3), "l"(db), "r"(acc), "n"(TB));
}

__device__ __forceinline__ void wgmma_n128_ss(float* d, uint64_t da, uint64_t db, int acc) {
    asm volatile(
        "{\n.reg .pred p;\nsetp.ne.b32 p, %66, 0;\n"
        "wgmma.mma_async.sync.aligned.m64n128k16.f32.bf16.bf16 {"
        "%0, %1, %2, %3, %4, %5, %6, %7, %8, %9, %10, %11, %12, %13, %14, %15, "
        "%16, %17, %18, %19, %20, %21, %22, %23, %24, %25, %26, %27, %28, %29, %30, %31, "
        "%32, %33, %34, %35, %36, %37, %38, %39, %40, %41, %42, %43, %44, %45, %46, %47, "
        "%48, %49, %50, %51, %52, %53, %54, %55, %56, %57, %58, %59, %60, %61, %62, %63"
        "}, %64, %65, p, 1, 1, 0, 1;\n}\n"
        :
        "+f"(d[0]), "+f"(d[1]), "+f"(d[2]), "+f"(d[3]), "+f"(d[4]), "+f"(d[5]), "+f"(d[6]), "+f"(d[7]),
        "+f"(d[8]), "+f"(d[9]), "+f"(d[10]), "+f"(d[11]), "+f"(d[12]), "+f"(d[13]), "+f"(d[14]), "+f"(d[15]),
        "+f"(d[16]), "+f"(d[17]), "+f"(d[18]), "+f"(d[19]), "+f"(d[20]), "+f"(d[21]), "+f"(d[22]), "+f"(d[23]),
        "+f"(d[24]), "+f"(d[25]), "+f"(d[26]), "+f"(d[27]), "+f"(d[28]), "+f"(d[29]), "+f"(d[30]), "+f"(d[31]),
        "+f"(d[32]), "+f"(d[33]), "+f"(d[34]), "+f"(d[35]), "+f"(d[36]), "+f"(d[37]), "+f"(d[38]), "+f"(d[39]),
        "+f"(d[40]), "+f"(d[41]), "+f"(d[42]), "+f"(d[43]), "+f"(d[44]), "+f"(d[45]), "+f"(d[46]), "+f"(d[47]),
        "+f"(d[48]), "+f"(d[49]), "+f"(d[50]), "+f"(d[51]), "+f"(d[52]), "+f"(d[53]), "+f"(d[54]), "+f"(d[55]),
        "+f"(d[56]), "+f"(d[57]), "+f"(d[58]), "+f"(d[59]), "+f"(d[60]), "+f"(d[61]), "+f"(d[62]), "+f"(d[63])
        : "l"(da), "l"(db), "r"(acc));
}

__device__ __forceinline__ void wgmma_n8_ta(float* d, uint64_t da, uint64_t db) {
    asm volatile("wgmma.mma_async.sync.aligned.m64n8k16.f32.bf16.bf16 {%0, %1, %2, %3}, %4, %5, 1, 1, 1, 1, 0;\n"
                 : "+f"(d[0]), "+f"(d[1]), "+f"(d[2]), "+f"(d[3]) : "l"(da), "l"(db));
}

__device__ __forceinline__ void wgmma_n8(float* d, uint64_t da, uint64_t db) {
    asm volatile("wgmma.mma_async.sync.aligned.m64n8k16.f32.bf16.bf16 {%0, %1, %2, %3}, %4, %5, 1, 1, 1, 0, 0;\n"
                 : "+f"(d[0]), "+f"(d[1]), "+f"(d[2]), "+f"(d[3]) : "l"(da), "l"(db));
}

#define PROF(slot, role)
#undef PROF_GT
#define PROF_GT(slot)

struct Params {
    const __nv_bfloat16* x;
    const __nv_bfloat16* w_r;
    const uint8_t *c_kv, *w_uk, *w_uv, *w_o;
};
__device__ __forceinline__ void lsu_prefetch(const void* p) { asm volatile("prefetch.global.L2 [%0];" ::"l"(p) : "memory"); }

template <typename T>
__device__ __forceinline__ T* ptr_off(T* base, uint32_t off) {
    uint32_t lo, hi;
    asm("mov.b64 {%0, %1}, %2;" : "=r"(lo), "=r"(hi) : "l"(base));
    asm("add.cc.u32 %0, %0, %2;\naddc.u32 %1, %1, 0;" : "+r"(lo), "+r"(hi) : "r"(off));
    T* r;
    asm("mov.b64 %0, {%1, %2};" : "=l"(r) : "r"(lo), "r"(hi));
    return r;
}
__device__ __forceinline__ int attn_rowblock(int pair, int seg) {
    int j = pair & 3, hl = pair >> 2;
    return (((hl & 1) | (j == 0)) ^ seg) ? j : 7 - j;
}
__device__ __forceinline__ int diag_place(int n, int i) {
    return (n >> 1) - 1 + (n < 6 ? i : 2 * i);
}
__device__ __forceinline__ int outproj_head(int i, int ib) {
    if (i < 16) return i;
    return 16 + 2 * (i & 7) + ((ib < 4) ^ ((i >> 3) & 1));
}

__device__ __forceinline__ void pin_value(uint32_t& v) { asm volatile("" : "+r"(v)); }
__device__ __forceinline__ void pin_value(int& v) { asm volatile("" : "+r"(v)); }
__device__ __forceinline__ void pin_value(const uint8_t*& v) { asm volatile("" : "+l"(v)); }

__device__ __forceinline__ void producer(const Params& P, uint32_t sb, int pair, int c,
                                         const CUtensorMap* m_ckv, const CUtensorMap* m_wuk, const CUtensorMap* m_wuv,
                                         const CUtensorMap* m_wq, const CUtensorMap* m_wo, const CUtensorMap* m_x,
                                         const CUtensorMap* m_out) {
    const int hl = pair >> 2;
    const int ibA = attn_rowblock(pair, 0), nA = 2 * ibA + 2;
    const int ib = (pair >> 1) & 7, mi = 2 * ib + c, nb = (pair >> 4) * 4 + (pair & 1) * 2;
    const bool leader = elect_one();
    uint32_t g = 4, tail = 0;
    if (leader) prefetch_map(m_wq);
    auto wait_released = [&](uint32_t need) {
#pragma unroll 1
        for (; tail <= need; tail++) mbar_wait(sb + BAR_EMPTY + (tail & 7) * 8, (tail >> 3) & 1);
    };
    auto wait_released_here = [&](uint32_t need) {
#pragma unroll 1
        for (; tail < need; tail++) mbar_wait(sb + BAR_EMPTY + (tail & 7) * 8, (tail >> 3) & 1);
        if (tail == need) mbar_wait(sb + BAR_EMPTYL + (need & 7) * 8, (need >> 3) & 1);
    };
    auto wait_released_peer = [&](uint32_t need) {
        if (tail == need) {
            uint32_t eb = sb + BAR_EMPTY + (need & 7) * 8, ep = (need >> 3) & 1;
            tail++;
            mbar_wait(eb, ep);
        }
    };
    auto full_bar = [&]() { return sb + BAR_FULL + (g & 7) * 8; };
    auto pin = [](auto&... v) { (pin_value(v), ...); };
#pragma unroll 1
    for (int rnd = 0; rnd < 2; rnd++) {
#pragma unroll 1
        for (int i = rnd ? 0 : 4; i < 16; i++) {
            const bool fresh = (i >> 2) != 2;
            int kb = (i ^ (i >> 1 & 4)) & 7, h2 = ((pair & 15) + rnd * 16) * 2 + c, krow = kb * 64, tok = (pair >> 4) * 512 + (i & 8) * 32 + c * 128;
            uint32_t pg = sb + (i & 3) * (3 * PAGE), pb = pg + (1 + c) * PAGE, bar = full_bar();
            pin(kb, h2, krow, tok, pg, pb, bar);
            const uint32_t need = g - 4 - (i < 2);
            wait_released_here(need);
            if (leader) {
                mbar_expect_tx(bar, fresh ? 3 * PAGE : 2 * PAGE);
                if (fresh) {
                    tma_3d(pg, m_wuk, 0, krow, h2, bar);
                    tma_3d(pg + 8192, m_wuv, 0, krow, h2, bar);
                }
            }
            wait_released_peer(need);
            if (leader) {
                tma_3d_mc(pb, m_ckv, 0, tok, kb, bar);
                if (rnd == 1 && i == 3) asm volatile("red.relaxed.gpu.global.add.u32 [%0], 1;" ::"l"(ptr_off(g_sync.kvfree, hl * 32)) : "memory");
            }
            g++;
        }
        mbar_sleep(sb + BAR_DEP, 0);
        const uint8_t* xa = ptr_off(g_xn, ibA * (16 * 32768) + c * PAGE);
        const uint8_t* xb = ptr_off(g_xn, (7 - ibA) * (16 * 32768) + (1 - c) * PAGE);
#pragma unroll 1
        for (int kb = 0; kb < DM / 64; kb++) {
            uint32_t pg = sb + (kb & 3) * (3 * PAGE), pw = pg + 2 * PAGE + c * 8192, bar = full_bar(), p2 = pg + PAGE;
            int krow = kb * 64;
            pin(pg, pw, p2, bar, krow);
            wait_released_here(g - 4);
            if (leader) {
                mbar_expect_tx(bar, 3 * PAGE);
                bulk_load(pg, xa, PAGE, bar);
            }
            wait_released_peer(g - 4);
            if (leader) {
                tma_3d_mc(pw, m_wq, 0, krow, (rnd * 16 + hl) * 2 + c, bar);
                bulk_load(p2, xb, PAGE, bar);
            }
            g++;
            xa += 32768;
            xb += 32768;
        }
        mbar_sleep(sb + BAR_DEP + 8 + rnd * 16, 0);
        if (rnd == 1 && leader) prefetch_map(m_wo);
        uint32_t pg = sb + c * PAGE;
#pragma unroll 1
        for (int j = 0; j < 36; j++) {
            const bool isk = j == 0 || ((j & 1) && j != 35);
            const int t = isk ? (j + 1) >> 1 : (j - 1) >> 1;
            const int n = t >= nA ? 18 - nA : nA, u = t >= nA ? t - nA : t, p1 = diag_place(n, 0), p2 = diag_place(n, 1);
            const int blk = u == p1 ? n - 2 : u == p2 ? n - 1 : u - (u > p1) - (u > p2);
            const uint8_t* src = ptr_off(g_kv, (hl * 16 + blk) * 65536 + (isk ? 0 : 32768) + c * PAGE);
            uint32_t bar = full_bar(), need = g - 6 + (j < 2) + (j < 5);
            pin(src, bar, need);
            wait_released(need);
            if (leader) {
                mbar_expect_tx(bar, 2 * PAGE);
                bulk_load_mc(pg, src, PAGE, bar);
            }
            g++;
            if (rnd == 0 && j >= 22 && j < 30) {
                const int cta = pair * 2 + c, i = j - 22;
                const uint32_t l = (threadIdx.x & 31) * 128;
                lsu_prefetch(ptr_off(i & 1 ? P.w_uv : P.w_uk, cta * 32768 + (i >> 1) * 8192 + 4096 + l));
            }
            if (rnd == 1 && j >= 32) {
                const int cta = pair * 2 + c, i = j - 32;
                const uint32_t l = (threadIdx.x & 31) * 128;
                lsu_prefetch(ptr_off(P.w_o, (i * 128 + cta) * 4096 + l));
            }
            pg = pg >= sb + SM_REGION - 2 * PAGE ? pg - (SM_REGION - 2 * PAGE) : pg + 2 * PAGE;
        }
    }
    uint32_t pg = sb;
#pragma unroll 1
    for (int i = 0; i < 64; i++) {
        if (i == 32 && leader) { prefetch_map(m_x); prefetch_map(m_out); }
        if ((i & 15) == 0 && i != 16) mbar_sleep(sb + BAR_DEP + 32 + (i >> 1) - (i ? 8 : 0), 0);
        const int kb = outproj_head(i >> 1, ib) * 2 + (i & 1);
        const uint8_t* src = ptr_off(g_ctx, (mi * 64 + kb) * PAGE);
        uint32_t bar = full_bar(), pw = pg + PAGE + c * 8192;
        int krow = kb * 2;
        pin(src, bar, pw, krow);
        wait_released_here(g - 6);
        if (leader) {
            mbar_expect_tx(bar, 2 * PAGE);
            bulk_load(pg, src, PAGE, bar);
        }
        wait_released_peer(g - 6);
        if (leader) tma_5d_mc(pw, m_wo, (nb + c) * 64, krow, bar);
        g++;
        pg = pg == sb + SM_REGION - 2 * PAGE ? sb : pg + 2 * PAGE;
    }
    const uint32_t bar = full_bar();
    wait_released(g - 6);
    if (leader) {
        mbar_expect_tx(bar, 2 * PAGE);
        tma_3d(pg, m_x, 0, mi * 128, nb, bar);
        tma_3d(pg + PAGE, m_x, 0, mi * 128 + 64, nb, bar);
    }
}

__device__ __forceinline__ uint32_t xn_block(int row64, int kb) {
    return (((row64 >> 2) * 16 + kb) * 4 + ((row64 & 1) * 2 + (((row64 >> 1) & 1) ^ 1))) * 8192;
}
__device__ __forceinline__ uint32_t image_offset(int row, int ch) {
    return xn_block(row >> 6, ch >> 3) + (row & 63) * 128 + (((ch & 7) ^ (row & 7)) << 4);
}
__device__ __forceinline__ uint32_t bf2_sub(uint32_t a, uint32_t b) {
    uint32_t r;
    asm("sub.rn.bf16x2 %0, %1, %2;" : "=r"(r) : "r"(a), "r"(b));
    return r;
}
__device__ __forceinline__ uint32_t bf2_fma(uint32_t a, uint32_t b, uint32_t c) {
    uint32_t r;
    asm("fma.rn.bf16x2 %0, %1, %2, %3;" : "=r"(r) : "r"(a), "r"(b), "r"(c));
    return r;
}
template <int N0, int N>
__device__ __forceinline__ void ln_sums(const uint32_t (&u)[N], float& sum, float& sq) {
    float s0 = 0.f, s1 = 0.f, q0 = 0.f, q1 = 0.f;
#pragma unroll
    for (int k = N0; k < N0 + 16; k++) {
        const float a = bf_lo(u[k]), b = bf_hi(u[k]);
        s0 += a; s1 += b;
        q0 = fmaf(a, a, q0); q1 = fmaf(b, b, q1);
    }
    sum = s0 + s1;
    sq = q0 + q1;
}
__device__ __forceinline__ void ln_finish(float sum, float sq, uint32_t& mean2, uint32_t& rhi2, uint32_t& rlo2) {
    const float ms = sum * (1.0f / DM);
    const float var = fmaxf(fmaf(-ms, ms, sq * (1.0f / DM)), 0.f);
    const float rden = rcp_approx(bf_round(sqrt_approx(bf_round(bf_round(var) + 1e-5f))));
    const float rhi = bf_round(rden);
    mean2 = pack_bf16(ms, ms);
    rhi2 = pack_bf16(rhi, rhi);
    rlo2 = pack_bf16(rden - rhi, rden - rhi);
}
template <int N0, int N>
__device__ __forceinline__ void ln_apply(const uint32_t (&u)[N], uint32_t mean2, uint32_t rhi2, uint32_t rlo2, uint8_t* dst) {
#pragma unroll
    for (int i = 0; i < 4; i++) {
        uint32_t o[4];
#pragma unroll
        for (int k = 0; k < 4; k++) {
            const uint32_t d = bf2_sub(u[N0 + 4 * i + k], mean2);
            o[k] = bf2_fma(d, rhi2, bf2_mul(d, rlo2));
        }
        __stcg(reinterpret_cast<uint4*>(dst + i * 131072), make_uint4(o[0], o[1], o[2], o[3]));
    }
}
__device__ __forceinline__ int query_rowblock(int pair, int c, int w, int seg) {
    const int qA = (w ? 0 : 2) + c;
    return 4 * attn_rowblock(pair, seg) + (seg ? 3 - qA : qA);
}

__device__ __forceinline__ void fetch_helper(const uint8_t* c_kv, uint32_t sb, int w, int lane, int pair, int c) {
    const uint32_t page = sb + SM_REGION + w * PAGE + lane * 16;
    mbar_sleep(sb + BAR_FULL + 5 * 8, 0);
    lsu_prefetch(ptr_off(c_kv, (pair >> 4) * 524288 + 262144 + ((pair & 15) * 4 + c * 2 + w) * 4096 + lane * 128));
    const unsigned e1 = __ldcg(&g_sync.done) / NCTA + 1;
#pragma unroll 1
    for (int e = 1; e <= 7; e += 2) mbar_sleep(sb + BAR_DONE + 8, (e >> 1) & 1);
    const int rb = ((pair >> 1) & 7) * 4 + c * 2 + w, kb0 = (pair >> 4) * 4 + (pair & 1) * 2;
    const uint8_t* src = ptr_off(g_xn, xn_block(rb, kb0) + lane * 16);
#pragma unroll 1
    for (int i = 0; i < 32; i += 4) {
#pragma unroll
        for (int k = 0; k < 4; k++) cp_async16(page + (i + k) * 512, src + (i + k) * 512 + (i >> 4) * (32768 - 8192));
        __nanosleep(200);
    }
    wait_counter(&g_sync.ffn_done, e1);
    const int r = __ldcg(ptr_off(g_sel, (lane >> 4) * 4)) - rb * 64, ch = lane & 15;
    const uint4 t = __ldcg(ptr_off(g_routed, ((lane >> 4) * 128 + kb0 * 8 + ch) * 16));
    asm volatile("cp.async.wait_all;" ::: "memory");
    __syncwarp();
    if (r >= 0 && r < 64)
        sts128(sb + SM_REGION + w * PAGE + (ch >> 3) * 8192 + r * 128 + (((ch & 7) ^ (r & 7)) << 4), t.x, t.y, t.z, t.w);
    __syncwarp();
    if (lane == 0) mbar_arrive(sb + BAR_G + w * 8);
    PROF(20, 2);
}

__device__ __noinline__ void sync_helper(uint32_t sb, int lane, int pair, int c) {
    const unsigned e1 = __ldcg(&g_sync.done) / NCTA + 1;
    const int ib = (pair >> 1) & 7;
    int e = 0, b = 0;
#pragma unroll 1
    for (uint32_t n = 0; (e < 9 || b < 7) && n < SPIN_LIMIT; n++) {
        if (e < 9 && __all_sync(~0u, mbar_test(sb + BAR_DONE + (e & 1) * 8, (e >> 1) & 1))) {
            const int rnd = e > 4, ev = (e - 1) & 3;
            unsigned* flag = e == 0 ? &g_sync.ln
                           : ev < 2 ? ptr_off(g_sync.kv, (rnd * 16 + (pair & 15)) * 32)
                                    : ptr_off(g_sync.ctx, (query_rowblock(pair, c, lane & 1, ev & 1) * NH + rnd * 16 + (pair >> 2)) * 4);
            asm volatile("fence.proxy.async.global;\nfence.release.gpu;" ::: "memory");
            if (lane < ((e == 0 || ev < 2) ? 1 : 2)) asm volatile("red.relaxed.gpu.global.add.u32 [%0], 1;" ::"l"(flag) : "memory");
            PROF(10 + e, 2);
            e++;
        }
        if (b < 7 && e > 0 && (b < 4 || (n & POLL_MASK) == 0)) {
            const int i = b == 4 ? lane >> 1 : 8 * b - 24 + ((lane >> 1) & 7);
            const unsigned* cnt = b == 0 ? &g_sync.ln
                                : b == 2 ? ptr_off(g_sync.kvfree, (pair & 15) * 32)
                                : b < 4 ? ptr_off(g_sync.kv, ((b >> 1) * 16 + (pair >> 2)) * 32)
                                        : ptr_off(g_sync.ctx, ((4 * ib + 2 * c + (lane & 1)) * NH + outproj_head(i & 31, ib)) * 4);
            if (__all_sync(~0u, (int)(ld_relaxed(cnt) - e1 * (b == 0 ? NMAIN : b == 2 ? 8 : b < 4 ? 16 : 1)) >= 0)) {
                asm volatile("fence.acquire.gpu;\nfence.proxy.async.global;" ::: "memory");
                __syncwarp();
                if (lane == 0) mbar_arrive(sb + BAR_DEP + b * 8);
                PROF(1 + b, 2);
                b++;
            }
        }
        __nanosleep(150);
    }
}

__device__ __forceinline__ unsigned long long block_max_key(unsigned long long k, unsigned long long* red, int tid) {
#pragma unroll
    for (int o = 16; o; o >>= 1) {
        unsigned long long t = __shfl_xor_sync(~0u, k, o);
        k = t > k ? t : k;
    }
    bar_sync(1, 256);
    if ((tid & 31) == 0) red[tid >> 5] = k;
    bar_sync(1, 256);
    k = red[0];
#pragma unroll
    for (int i = 1; i < 8; i++) k = red[i] > k ? red[i] : k;
    return k;
}

constexpr int FS = FF / 4;
constexpr int FSTAGE = 32768, FNST = 6;
constexpr int FN0 = 32, FN1 = 2 * (DM / 16), FN2 = FS / 16;
constexpr uint32_t XB = FNST * FSTAGE, HB = XB + 16384, AUX = HB + 14336, PAUSE = AUX + 192;
constexpr int PAUSE_AT = 100;

__device__ __forceinline__ void ffn_producer(uint32_t sb, int s, unsigned e1, const CUtensorMap* m_gate, const CUtensorMap* m_up,
                                             const CUtensorMap* m_down) {
    const uint64_t pol = policy_evict_first();
    int slot = 0, ph = 1;
    wait_counter(&g_sync.ln, e1 * NMAIN);
#pragma unroll 1
    for (int st = -FN0; st < FN1 + FN2; st++) {
        mbar_sleep(sb + BAR_EMPTY + slot * 8, ph);
        const uint32_t bar = sb + BAR_FULL + slot * 8;
        if (st < 0) {
            mbar_expect_tx(bar, FSTAGE);
            bulk_load(sb + slot * FSTAGE, ptr_off(g_xn, (s * FN0 + FN0 + st) * FSTAGE), FSTAGE, bar);
        } else {
            if (st >= PAUSE_AT) {
                uint32_t p;
                for (uint32_t n = 0; n < 100; n++) {
                    asm volatile("ld.volatile.shared.u32 %0, [%1];" : "=r"(p) : "r"(sb + PAUSE) : "memory");
                    if (!p) break;
                    __nanosleep(200);
                }
            }
            const bool up = st < FN1;
            mbar_expect_tx(bar, up ? FS * 32 : DM * 32);
            tma_3d_hint(sb + slot * FSTAGE, up ? ((st & 1) ? m_up : m_gate) : m_down, 0,
                        up ? (st >> 1) * 16 : s * FS + (st - FN1) * 16, up ? s * (FS / 64) : 0, bar, pol);
        }
        if (++slot == FNST) { slot = 0; ph ^= 1; }
    }
}
__device__ __forceinline__ void ffn_pacer(uint32_t sb, unsigned e1) {
    wait_counter(&g_sync.kvfree[0], e1 * 8, 500);
    asm volatile("st.volatile.shared.u32 [%0], 1;" ::"r"(sb + PAUSE) : "memory");
    wait_counter(&g_sync.kv[16 * 8], e1 * 16, 500);
    asm volatile("st.volatile.shared.u32 [%0], 0;" ::"r"(sb + PAUSE) : "memory");
}

__device__ __forceinline__ void ffn_cta(uint8_t* smem, uint32_t sb, int s, unsigned epoch, const __nv_bfloat16* w_r) {
    const int tid = threadIdx.x, lane = tid & 31;
    const int warp = __shfl_sync(~0u, tid >> 5, 0), w = warp >> 2;
    unsigned long long* red = reinterpret_cast<unsigned long long*>(smem + AUX);
    unsigned* flag = reinterpret_cast<unsigned*>(smem + AUX + 128);
    const unsigned e1 = epoch + 1;
    for (int i = tid; i < (16384 + 14336) / 16; i += 256) reinterpret_cast<uint4*>(smem + XB)[i] = make_uint4(0, 0, 0, 0);
    int slot = 0, ph = 0, prev = 0;
    auto next_stage = [&](bool has_prev) {
        wg_commit();
        wg_wait<1>();
        if (has_prev && lane < 2) mbar_arrive(sb + BAR_EMPTY + prev * 8);
        prev = slot;
        if (++slot == FNST) { slot = 0; ph ^= 1; }
    };
    {
        bar_sync(1, 256);
        if (tid < 128) *reinterpret_cast<uint4*>(smem + XB + (tid >> 3) * 1024 + (tid & 7) * 16) = __ldg(reinterpret_cast<const uint4*>(w_r) + tid);
        fence_async_smem();
        bar_sync(1, 256);
#pragma unroll 1
        for (int blk = 0; blk < 2; blk++) {
            float ar[8];
#pragma unroll
            for (int i = 0; i < 8; i++) ar[i] = 0.f;
#pragma unroll 1
            for (int kb = 0; kb < 16; kb++) {
                const uint64_t db = make_desc(sb + XB + kb * 1024, 16);
                mbar_wait(sb + BAR_FULL + slot * 8, ph);
                const uint64_t da = make_desc(sb + slot * FSTAGE + w * 16384, 16);
                wg_fence();
#pragma unroll
                for (int q = 0; q < 4; q++) {
                    wgmma_n8(ar, da + 2 * q, db + 2 * q);
                    wgmma_n8(ar + 4, da + 512 + 2 * q, db + 2 * q);
                }
                next_stage(blk + kb > 0);
            }
            wg_wait<0>();
            reg_fence(ar);
            if ((lane & 3) == 0) {
#pragma unroll
                for (int i = 0; i < 4; i++)
                    __stcg(&g_r[(s * 2 + blk) * 256 + (w + 2 - (i & 2)) * 64 + (warp & 3) * 16 + (lane >> 2) + (i & 1) * 8], bf_round(ar[2 * i]));
            }
        }
        __threadfence();
        bar_sync(1, 256);
        if (tid == 0) {
            red_release(&g_sync.router);
            wait_counter(&g_sync.router, e1 * 4);
        }
        bar_sync(1, 256);
    }
    unsigned long long keys[8];
    unsigned long long best = 0;
#pragma unroll
    for (int i = 0; i < 8; i++) {
        int idx = tid + 256 * i;
        uint32_t b = __float_as_uint(__ldcg(&g_r[idx]) + 0.0f);
        b = (b & 0x80000000u) ? ~b : (b | 0x80000000u);
        keys[i] = ((unsigned long long)b << 32) | (unsigned)(SEQ - 1 - idx);
        best = keys[i] > best ? keys[i] : best;
    }
    const unsigned long long k0 = block_max_key(best, red, tid);
    best = 0;
#pragma unroll
    for (int i = 0; i < 8; i++) best = (keys[i] != k0 && keys[i] > best) ? keys[i] : best;
    const unsigned long long k1 = block_max_key(best, red, tid);
    const int row = SEQ - 1 - (int)((w ? k1 : k0) & 0xffffffffu);
    const int ch = tid & 127;
    const uint4 xrow = __ldcg(reinterpret_cast<const uint4*>(g_xn + image_offset(row, ch)));
    *reinterpret_cast<uint4*>(smem + XB + (ch >> 3) * 1024 + w * 128 + (((ch & 7) ^ w) << 4)) = xrow;
    fence_async_smem();
    bar_sync(1, 256);
    PROF(20, tid >> 7);
    {
        float ag[28], au[28];
#pragma unroll
        for (int i = 0; i < 28; i++) ag[i] = au[i] = 0.f;
#pragma unroll 1
        for (int ks = 0; ks < DM / 16; ks++) {
            const uint64_t db = make_desc(sb + XB + (ks >> 2) * 1024 + (ks & 3) * 32, 16);
            mbar_wait(sb + BAR_FULL + slot * 8, ph);
            uint64_t da = make_desc(sb + slot * FSTAGE + w * (7 * 2048), 16);
            wg_fence();
#pragma unroll
            for (int b = 0; b < 7; b++) wgmma_n8_ta(ag + 4 * b, da + b * 128, db);
            next_stage(true);
            mbar_wait(sb + BAR_FULL + slot * 8, ph);
            da = make_desc(sb + slot * FSTAGE + w * (7 * 2048), 16);
            wg_fence();
#pragma unroll
            for (int b = 0; b < 7; b++) wgmma_n8_ta(au + 4 * b, da + b * 128, db);
            next_stage(true);
        }
        wg_wait<0>();
        reg_fence(ag);
        reg_fence(au);
        if ((lane & 3) == 0) {
#pragma unroll
            for (int i = 0; i < 28; i++) {
                const int f = (warp & 3) * 16 + (lane >> 2) + (i & 2) * 4, tok = i & 1;
                const float h = bf_round(silu_f(bf_round(ag[i]))) * bf_round(au[i]);
                *reinterpret_cast<__nv_bfloat16*>(smem + HB + (w * 7 + (i >> 2)) * 1024 + tok * 128 + (((f >> 3) ^ tok) << 4) + (f & 7) * 2) =
                    __float2bfloat16_rn(h);
            }
        }
    }
    fence_async_smem();
    bar_sync(1, 256);
    PROF(21, tid >> 7);
    {
        float ay[32];
#pragma unroll
        for (int i = 0; i < 32; i++) ay[i] = 0.f;
#pragma unroll 1
        for (int ks = 0; ks < FN2; ks++) {
            const uint64_t db = make_desc(sb + HB + (ks >> 2) * 1024 + (ks & 3) * 32, 16);
            mbar_wait(sb + BAR_FULL + slot * 8, ph);
            const uint64_t da = make_desc(sb + slot * FSTAGE + w * (8 * 2048), 16);
            wg_fence();
#pragma unroll
            for (int b = 0; b < 8; b++) wgmma_n8_ta(ay + 4 * b, da + b * 128, db);
            next_stage(true);
        }
        wg_wait<0>();
        reg_fence(ay);
        if ((lane & 3) == 0) {
#pragma unroll
            for (int i = 0; i < 32; i++)
                g_ypart[(s * 2 + (i & 1)) * DM + (w * 8 + (i >> 2)) * 64 + (warp & 3) * 16 + (lane >> 2) + (i & 2) * 4] = ay[i];
        }
    }
    PROF(23, tid >> 7);
    __threadfence();
    bar_sync(1, 256);
    if (tid == 0) {
        *flag = atomicAdd(&g_sync.ffn_ticket, 1u) == epoch * 4 + 3;
        __threadfence();
    }
    bar_sync(1, 256);
    if (*flag) {
        const float sg = bf_round(__fdividef(1.0f, 1.0f + __expf(-__ldcg(&g_r[row]))));
        const uint32_t xu[4] = {xrow.x, xrow.y, xrow.z, xrow.w};
        uint32_t o[4];
#pragma unroll
        for (int k = 0; k < 4; k++) {
            float y0 = 0.f, y1 = 0.f;
#pragma unroll
            for (int q = 0; q < 4; q++) {
                const float2 y = __ldcg(reinterpret_cast<const float2*>(&g_ypart[(q * 2 + w) * DM + ch * 8 + 2 * k]));
                y0 += y.x; y1 += y.y;
            }
            o[k] = pack_bf16(bf_lo(xu[k]) + bf_round(bf_round(y0) * sg), bf_hi(xu[k]) + bf_round(bf_round(y1) * sg));
        }
        g_routed[w * 128 + ch] = make_uint4(o[0], o[1], o[2], o[3]);
        if (ch == 0) g_sel[w] = row;
        bar_sync(1, 256);
        if (tid == 0) red_release(&g_sync.ffn_done);
    }
}

__device__ __forceinline__ uint32_t slab_addr(uint32_t stg, int lane, int s) {
    const int row = ((lane >> 3) & 1) * 8 + (lane & 7);
    const int chunk = 2 * (s & 3) + (lane >> 4);
    return stg + row * 128 + (s >> 2) * 8192 + ((chunk ^ (lane & 7)) << 4);
}

constexpr float SM_SCALE = 0.08838834764831845f * 1.4426950408889634f;
constexpr float SUM_HI = 1048576.f, SUM_LO = 1.0f / 1048576.f;

template <int J0>
__device__ __forceinline__ void mask_half(float (&S)[64], float limf) {
    asm volatile("" : "+f"(limf));
#pragma unroll
    for (int i = 0; i < 32; i++) {
        const int j = i >> 2, key = 32 * (j >> 2) + 2 * (j & 3) + (i & 1) - 4 * (i & 2);
        float t;
        asm("add.sat.f32 %0, %1, %2;" : "=f"(t) : "f"((float)key), "f"(-limf));
        S[4 * J0 + i] = fmaf(t, -1e30f, S[4 * J0 + i]);
    }
}
__device__ __forceinline__ void issue_qk(float (&S)[64], const uint32_t (&Q)[32], uint64_t d0) {
#pragma unroll
    for (int s = 0; s < 8; s++)
        wgmma_n128_rs<1>(S, Q[4 * s], Q[4 * s + 1], Q[4 * s + 2], Q[4 * s + 3], d0 + s * 128, s > 0);
}
template <int S0, int S1>
__device__ __forceinline__ void issue_pv(float (&O)[64], const uint32_t (&Pm)[32], uint64_t d0, int acc) {
#pragma unroll
    for (int s = S0; s < S1; s++)
        wgmma_n128_rs<0>(O, Pm[4 * s], Pm[4 * s + 1], Pm[4 * s + 2], Pm[4 * s + 3], d0 + (s >> 2) * (PAGE >> 4) + (s & 3) * 2, s > 0 ? 1 : acc);
}
template <int J0, int J1>
__device__ __forceinline__ void exp_part(const float (&S)[64], uint32_t (&Pm)[32], float (&sum)[4]) {
#pragma unroll
    for (int i = 2 * J0; i < 2 * J1; i++) asm volatile("" : "+r"(Pm[i])::"memory");
#pragma unroll
    for (int j = J0; j < J1; j++) {
        const float e0 = ex2(S[4 * j]), e1 = ex2(S[4 * j + 1]), e2 = ex2(S[4 * j + 2]), e3 = ex2(S[4 * j + 3]);
        sum[0] += e0; sum[1] += e1; sum[2] += e2; sum[3] += e3;
        Pm[2 * j] = pack_bf16(e0, e1);
        Pm[2 * j + 1] = pack_bf16(e2, e3);
    }
}
__device__ __forceinline__ void shift_rows(float (&S)[64], float d0, float d1) {
#pragma unroll
    for (int j = 0; j < 16; j++) {
        S[4 * j] -= d0; S[4 * j + 1] -= d0; S[4 * j + 2] -= d1; S[4 * j + 3] -= d1;
    }
}
__device__ __forceinline__ void sched_fence(uint32_t& tick, bool on) {
    asm volatile("{\n.reg .pred p;\nsetp.ne.u32 p, %1, 0;\n@p mov.u32 %0, %%clock;\n}\n" : "+r"(tick) : "r"((uint32_t)on) : "memory");
}
constexpr int LAG = 4;
struct NoExtra { __device__ __forceinline__ void operator()(int) const {} };
template <int K0, int K1, int NP, int WAITAT, typename X = NoExtra>
__device__ __forceinline__ void exp_stages(const float (&S)[64], float (&e)[64], uint32_t (&Pm)[32], float (&sum)[4], uint32_t& tick, bool on,
                                           X extra = X()) {
#pragma unroll
    for (int k = K0; k < K1; k++) {
        if (k == WAITAT) wg_wait<1>();
        if (k < NP) {
            asm volatile("ex2.approx.ftz.f32 %0, %1;" : "=f"(e[2 * k]) : "f"(S[2 * k]));
            asm volatile("ex2.approx.ftz.f32 %0, %1;" : "=f"(e[2 * k + 1]) : "f"(S[2 * k + 1]));
        }
        if (k >= LAG) {
            const int i = 2 * (k - LAG);
            asm volatile("add.f32 %0, %0, %1;" : "+f"(sum[i & 3]) : "f"(e[i]));
            asm volatile("add.f32 %0, %0, %1;" : "+f"(sum[(i & 3) + 1]) : "f"(e[i + 1]));
            asm volatile("cvt.rn.bf16x2.f32 %0, %1, %2;" : "=r"(Pm[i / 2]) : "f"(e[i + 1]), "f"(e[i]));
        }
        extra(k);
        if (k >= LAG - 1 && k < NP - 1 && k != K1 - 1) sched_fence(tick, on);
    }
}
__device__ constexpr int chunk_src(int i) { return 4 * (4 * (i >> 3) + (i & 3)) + 2 * ((i >> 2) & 1); }
enum : uint32_t { CTL_START = 1, CTL_SWITCH = 2, CTL_DIRECT = 4, CTL_HALF = 8, CTL_MASKHI = 16, CTL_LOADQ = 32, CTL_PVHALF = 64, CTL_PVACC = 128,
                  CTL_SKIPREL = 256 };
__device__ __forceinline__ float quad_sum(float v) {
    v += __shfl_xor_sync(~0u, v, 1);
    return v + __shfl_xor_sync(~0u, v, 2);
}

__device__ __forceinline__ void store_part(uint8_t* d0, int p, const uint32_t (&pk)[64]) {
    asm volatile("{\n.reg .b64 d1;\nxor.b64 d1, %0, 64;\n"
                 "TS: .branchtargets P0, P1, P2, P3, P4, P5, P6, P7;\n"
                 "brx.idx.uni %1, TS;\n"
                 "P0:\n st.global.cg.v4.u32 [%0 + 0], {%2, %3, %4, %5};\n st.global.cg.v4.u32 [d1 + 0], {%10, %11, %12, %13};\n bra.uni DONE;\n"
                 "P1:\n st.global.cg.v4.u32 [%0 + 1024], {%6, %7, %8, %9};\n st.global.cg.v4.u32 [d1 + 1024], {%14, %15, %16, %17};\n bra.uni DONE;\n"
                 "P2:\n st.global.cg.v4.u32 [%0 + 16384], {%18, %19, %20, %21};\n st.global.cg.v4.u32 [d1 + 16384], {%26, %27, %28, %29};\n bra.uni DONE;\n"
                 "P3:\n st.global.cg.v4.u32 [%0 + 17408], {%22, %23, %24, %25};\n st.global.cg.v4.u32 [d1 + 17408], {%30, %31, %32, %33};\n bra.uni DONE;\n"
                 "P4:\n st.global.cg.v4.u32 [%0 + 65536], {%34, %35, %36, %37};\n st.global.cg.v4.u32 [d1 + 65536], {%42, %43, %44, %45};\n bra.uni DONE;\n"
                 "P5:\n st.global.cg.v4.u32 [%0 + 66560], {%38, %39, %40, %41};\n st.global.cg.v4.u32 [d1 + 66560], {%46, %47, %48, %49};\n bra.uni DONE;\n"
                 "P6:\n st.global.cg.v4.u32 [%0 + 81920], {%50, %51, %52, %53};\n st.global.cg.v4.u32 [d1 + 81920], {%58, %59, %60, %61};\n bra.uni DONE;\n"
                 "P7:\n st.global.cg.v4.u32 [%0 + 82944], {%54, %55, %56, %57};\n st.global.cg.v4.u32 [d1 + 82944], {%62, %63, %64, %65};\n bra.uni DONE;\n"
                 "DONE:\n}\n"
                 ::"l"(d0), "r"(p), "r"(pk[0]), "r"(pk[1]), "r"(pk[2]), "r"(pk[3]), "r"(pk[4]), "r"(pk[5]), "r"(pk[6]), "r"(pk[7]), "r"(pk[8]), "r"(pk[9]), "r"(pk[10]), "r"(pk[11]), "r"(pk[12]), "r"(pk[13]), "r"(pk[14]), "r"(pk[15]), "r"(pk[16]), "r"(pk[17]), "r"(pk[18]), "r"(pk[19]), "r"(pk[20]), "r"(pk[21]), "r"(pk[22]), "r"(pk[23]), "r"(pk[24]), "r"(pk[25]), "r"(pk[26]), "r"(pk[27]), "r"(pk[28]), "r"(pk[29]), "r"(pk[30]), "r"(pk[31]), "r"(pk[32]), "r"(pk[33]), "r"(pk[34]), "r"(pk[35]), "r"(pk[36]), "r"(pk[37]), "r"(pk[38]), "r"(pk[39]), "r"(pk[40]), "r"(pk[41]), "r"(pk[42]), "r"(pk[43]), "r"(pk[44]), "r"(pk[45]), "r"(pk[46]), "r"(pk[47]), "r"(pk[48]), "r"(pk[49]), "r"(pk[50]), "r"(pk[51]), "r"(pk[52]), "r"(pk[53]), "r"(pk[54]), "r"(pk[55]), "r"(pk[56]), "r"(pk[57]), "r"(pk[58]), "r"(pk[59]), "r"(pk[60]), "r"(pk[61]), "r"(pk[62]), "r"(pk[63])
                 : "memory");
}

__device__ __forceinline__ void store_part4(uint8_t* d0, int p, const uint32_t (&pk)[64]) {
    asm volatile("{\n.reg .b64 d1;\nxor.b64 d1, %0, 64;\n"
                 "TS: .branchtargets P0, P1, P2, P3;\n"
                 "brx.idx.uni %1, TS;\n"
                 "P0:\n st.global.cg.v4.u32 [%0 + 0], {%2, %3, %4, %5};\n st.global.cg.v4.u32 [d1 + 0], {%10, %11, %12, %13};\n bra.uni DONE;\n"
                 "P1:\n st.global.cg.v4.u32 [%0 + 1024], {%6, %7, %8, %9};\n st.global.cg.v4.u32 [d1 + 1024], {%14, %15, %16, %17};\n bra.uni DONE;\n"
                 "P2:\n st.global.cg.v4.u32 [%0 + 16384], {%18, %19, %20, %21};\n st.global.cg.v4.u32 [d1 + 16384], {%26, %27, %28, %29};\n bra.uni DONE;\n"
                 "P3:\n st.global.cg.v4.u32 [%0 + 17408], {%22, %23, %24, %25};\n st.global.cg.v4.u32 [d1 + 17408], {%30, %31, %32, %33};\n bra.uni DONE;\n"
                 "DONE:\n}\n"
                 ::"l"(d0), "r"(p), "r"(pk[0]), "r"(pk[1]), "r"(pk[2]), "r"(pk[3]), "r"(pk[4]), "r"(pk[5]), "r"(pk[6]), "r"(pk[7]), "r"(pk[8]), "r"(pk[9]), "r"(pk[10]), "r"(pk[11]), "r"(pk[12]), "r"(pk[13]), "r"(pk[14]), "r"(pk[15]), "r"(pk[16]), "r"(pk[17]), "r"(pk[18]), "r"(pk[19]), "r"(pk[20]), "r"(pk[21]), "r"(pk[22]), "r"(pk[23]), "r"(pk[24]), "r"(pk[25]), "r"(pk[26]), "r"(pk[27]), "r"(pk[28]), "r"(pk[29]), "r"(pk[30]), "r"(pk[31])
                 : "memory");
}

__device__ __forceinline__ void set_quad(uint32_t (&d)[32], int p, uint32_t u0, uint32_t u1, uint32_t u2, uint32_t u3) {
    asm volatile("{\nTG: .branchtargets G0, G1, G2, G3, G4, G5, G6, G7;\n"
                 "brx.idx.uni %32, TG;\n"
                 "G0:\n mov.b32 %0, %33;\n mov.b32 %1, %34;\n mov.b32 %2, %35;\n mov.b32 %3, %36;\n bra.uni DONE;\n"
                 "G1:\n mov.b32 %4, %33;\n mov.b32 %5, %34;\n mov.b32 %6, %35;\n mov.b32 %7, %36;\n bra.uni DONE;\n"
                 "G2:\n mov.b32 %8, %33;\n mov.b32 %9, %34;\n mov.b32 %10, %35;\n mov.b32 %11, %36;\n bra.uni DONE;\n"
                 "G3:\n mov.b32 %12, %33;\n mov.b32 %13, %34;\n mov.b32 %14, %35;\n mov.b32 %15, %36;\n bra.uni DONE;\n"
                 "G4:\n mov.b32 %16, %33;\n mov.b32 %17, %34;\n mov.b32 %18, %35;\n mov.b32 %19, %36;\n bra.uni DONE;\n"
                 "G5:\n mov.b32 %20, %33;\n mov.b32 %21, %34;\n mov.b32 %22, %35;\n mov.b32 %23, %36;\n bra.uni DONE;\n"
                 "G6:\n mov.b32 %24, %33;\n mov.b32 %25, %34;\n mov.b32 %26, %35;\n mov.b32 %27, %36;\n bra.uni DONE;\n"
                 "G7:\n mov.b32 %28, %33;\n mov.b32 %29, %34;\n mov.b32 %30, %35;\n mov.b32 %31, %36;\n bra.uni DONE;\n"
                 "DONE:\n}\n"
                 : "+r"(d[0]), "+r"(d[1]), "+r"(d[2]), "+r"(d[3]), "+r"(d[4]), "+r"(d[5]), "+r"(d[6]), "+r"(d[7]), "+r"(d[8]), "+r"(d[9]), "+r"(d[10]), "+r"(d[11]), "+r"(d[12]), "+r"(d[13]), "+r"(d[14]), "+r"(d[15]), "+r"(d[16]), "+r"(d[17]), "+r"(d[18]), "+r"(d[19]), "+r"(d[20]), "+r"(d[21]), "+r"(d[22]), "+r"(d[23]), "+r"(d[24]), "+r"(d[25]), "+r"(d[26]), "+r"(d[27]), "+r"(d[28]), "+r"(d[29]), "+r"(d[30]), "+r"(d[31])
                 : "r"(p), "r"(u0), "r"(u1), "r"(u2), "r"(u3));
}

__device__ __forceinline__ void consumer(uint32_t sb, int pair, int c, const CUtensorMap* m_out, const uint8_t* x) {
    const int tid = threadIdx.x;
    const int warp = __shfl_sync(~0u, tid >> 5, 0);
    const int w = warp >> 2, v = warp & 3, lane = tid & 31;
    constexpr uint64_t desc_hi = ((uint64_t)(1024 >> 4) << 32) | (1ull << 62);

    const uint32_t empty_rel = lane == 2 ? mapa(sb + BAR_EMPTYL, c) : mapa(sb + BAR_EMPTY, lane & 1);
    auto release = [&](uint32_t grp) {
        if (lane < 3) mbar_arrive_cluster(empty_rel + (grp & 7) * 8);
    };
    auto wait_full = [&](uint32_t grp) { mbar_wait(sb + BAR_FULL + (grp & 7) * 8, (grp >> 3) & 1); };

    uint32_t g = 0;
    const uint32_t stg = sb + SM_REGION + w * PAGE + v * 2048;
    const uint32_t chunk0 = (lane >> 2) * 128 + (((lane & 3) ^ (lane >> 2)) << 4);
    uint32_t ndone = 0;
    auto mark_done = [&]() {
        __syncwarp();
        if (lane == 0) mbar_arrive(sb + BAR_DONE + ndone);
        ndone ^= 8;
    };
    auto ctx_dst = [&](int rnd, int seg) {
        const int rb = query_rowblock(pair, c, w, seg);
        return ptr_off(g_ctx, ((rb >> 1) * 64 + (rnd * 16 + (pair >> 2)) * 2) * PAGE + (rb & 1) * 8192 + v * 2048);
    };

    uint32_t ctl_tab;
    {
        const int t = lane, nA = 2 * attn_rowblock(pair, 0) + 2, nB = 18 - nA, firstB = nA - w;
        const int tA = w ? diag_place(nA, 0) : diag_place(nA, 1), tB = w ? nA + diag_place(nB, 1) - 1 : nA + diag_place(nB, 0);
        const int ts = w ? diag_place(nA, 1) - 1 : nA + diag_place(nB, 1) - 1;
        auto is_half = [&](int u) { return (u == tA && c == 0) || (u == tB && c == 1); };
        const bool diag = t == tA || t == tB;
        const int kadv = (t == 0 ? 1 : 2) + (t == ts ? 2 : 0);
        const int vadv = 2 + (t == ts + 1 ? 2 : 0) - (t == 16 ? 1 : 0);
        ctl_tab = (t == 0 ? CTL_START : 0) | (t == firstB ? CTL_SWITCH : 0) | (t == ts + 1 ? CTL_SKIPREL : 0) |
                  (diag ? (is_half(t) ? CTL_HALF : CTL_MASKHI) : 0) | (t == firstB - 1 ? (t ? CTL_LOADQ : CTL_DIRECT) : 0) |
                  ((t > 0 && is_half(t - 1)) ? CTL_PVHALF : 0) | ((t == 1 || t == firstB + 1) ? 0 : CTL_PVACC) |
                  (kadv << 16) | (vadv << 20);
    }

    uint32_t pk[64];
#pragma unroll
    for (int i = 0; i < 64; i++) pk[i] = 0;
    uint8_t* pend = nullptr;
    auto write_part = [&](int p) { store_part(pend, p, pk); };
    if (w == 1) bar_arrive(2, 256);
    asm volatile("barrier.cluster.wait.aligned;" ::: "memory");
    {
        const uint8_t* src = ptr_off(x, ((pair * 2 + c) * 16 + warp * 2) * (DM * 2) + lane * 16);
#pragma unroll
        for (int i = 0; i < 5; i++) {
            uint4 t;
            asm volatile("ld.global.cg.v4.u32 {%0, %1, %2, %3}, [%4];" : "=r"(t.x), "=r"(t.y), "=r"(t.z), "=r"(t.w) : "l"(src + i * 512) : "memory");
            pk[4 * i] = t.x; pk[4 * i + 1] = t.y; pk[4 * i + 2] = t.z; pk[4 * i + 3] = t.w;
        }
    }
    asm volatile("cp.async.wait_all;" ::: "memory");
    fence_async_smem();
    bar_sync(4, 256);

    float O[64], l[2] = {0.f, 0.f};
    auto finish_attention = [&](int rnd, uint32_t ge) {
        const float i0 = rcp_approx(quad_sum(l[0])), i1 = rcp_approx(quad_sum(l[1]));
        if (rnd) wg_wait<1>(); else wg_wait<0>();
        reg_fence(O);
        release(ge - 1);
#pragma unroll
        for (int i = 0; i < 32; i++) {
            const float sc = (i & 4) ? i1 : i0;
            pk[i] = pack_bf16(O[chunk_src(i)] * sc, O[chunk_src(i) + 1] * sc);
        }
        pend = ptr_off(ctx_dst(rnd, 1), chunk0);
#pragma unroll
        for (int i = 32; i < 64; i++) pk[i] = 0;
    };
    for (int item = 0;; item++) {
        if (item != 2 && item != 5) {
            constexpr int nk = DC / 64;
            float acc[128];
            auto issue_kblock = [&](int first_acc) {
                wait_full(g);
                const uint32_t pg = sb + (g & 3) * (3 * PAGE);
                const uint64_t da = make_desc(pg + w * 8192, 16), db = make_desc(pg + PAGE, 16);
                wg_fence();
#pragma unroll
                for (int q = 0; q < 4; q++) wgmma_n256_ss(acc, da + 128 * q, db + 2 * q, q ? 1 : first_acc);
                wg_commit();
                g++;
            };
            if (item == 0) PROF(17, w);
            issue_kblock(0);
            if (item == 0) PROF(1, w);
            if (item == 0 && w == 0) PROF_GT(1);
            const int nparts = item == 0 ? 0 : (item == 3 ? 4 : 8);
            const int ln_row = (pair * 2 + c) * 16 + warp * 2;
            if (item == 0) {
                const uint8_t* src = ptr_off(x, ln_row * (DM * 2) + lane * 16);
#pragma unroll
                for (int i = 5; i < 8; i++) {
                    const uint4 t = __ldcg(reinterpret_cast<const uint4*>(src + i * 512));
                    pk[4 * i] = t.x; pk[4 * i + 1] = t.y; pk[4 * i + 2] = t.z; pk[4 * i + 3] = t.w;
                }
            }
#pragma unroll 1
            for (int kb = 1; kb < nk; kb++) {
                if (kb == nk - 2 && w == 1) bar_sync(4, 256);
                issue_kblock(1);
                if (kb == nk - 1 && w == 0) bar_arrive(4, 256);
                if (kb <= nparts) {
                    if (item == 4 && kb == 1) mbar_wait(sb + BAR_DEP + 16, 0);
                    write_part(kb - 1);
                    if (kb == nk - 1) write_part(nk - 1);
                    if (kb == nparts || kb == nk - 1) mark_done();
                }
                wg_wait<1>();
                release(g - 2);
                if (g >= 4 && g <= 8) {
                    float s[2], q[2];
                    if (g == 4) {
                        ln_sums<0>(pk, s[0], q[0]);
                        pk[32] = __float_as_uint(s[0]); pk[33] = __float_as_uint(q[0]);
                    }
                    if (g == 5) {
                        ln_sums<16>(pk, s[1], q[1]);
                        pk[34] = __float_as_uint(s[1]); pk[35] = __float_as_uint(q[1]);
                    }
                    if (g == 6) {
#pragma unroll
                        for (int r = 0; r < 2; r++) { s[r] = __uint_as_float(pk[32 + 2 * r]); q[r] = __uint_as_float(pk[33 + 2 * r]); }
                        const bool hi = lane & 16, od = lane & 8;
                        float a = hi ? s[1] : s[0], b = hi ? q[1] : q[0];
                        a += __shfl_xor_sync(~0u, hi ? s[0] : s[1], 16);
                        b += __shfl_xor_sync(~0u, hi ? q[0] : q[1], 16);
                        float t = od ? b : a;
                        t += __shfl_xor_sync(~0u, od ? a : b, 8);
#pragma unroll
                        for (int o = 4; o; o >>= 1) t += __shfl_xor_sync(~0u, t, o);
#pragma unroll
                        for (int r = 0; r < 2; r++) {
                            s[r] = __shfl_sync(~0u, t, 16 * r);
                            q[r] = __shfl_sync(~0u, t, 16 * r + 8);
                        }
                        ln_finish(s[0], q[0], pk[36], pk[37], pk[38]);
                        ln_finish(s[1], q[1], pk[39], pk[40], pk[41]);
                    }
                    if (g == 7 + w) ln_apply<0>(pk, pk[36], pk[37], pk[38], ptr_off(g_xn, image_offset(ln_row, lane)));
                    if (g == 8) {
                        ln_apply<16>(pk, pk[39], pk[40], pk[41], ptr_off(g_xn, image_offset(ln_row + 1, lane)));
                        mark_done();
                    }
                }
            }
            wg_wait<0>();
            reg_fence(acc);
            release(g - 1);
            PROF(2 + 2 * item, w);
            if (w == 0) PROF_GT(2 + 2 * item);
            const int second = item == 1 || item == 4;
            if (w == 0) {
#pragma unroll
                for (int i = 0; i < 128; i++) acc[i] *= SM_SCALE;
            }
            reg_fence(acc);
#pragma unroll
            for (int i = 0; i < 64; i++) pk[i] = pack_bf16(acc[chunk_src(i)], acc[chunk_src(i) + 1]);
            pend = ptr_off(g_kv, ((pair & 15) * 16 + (pair >> 4) * 4 + second * 2) * 65536 + w * 32768 + c * 8192 + v * 2048 + chunk0);
            PROF(3 + 2 * item, w);
            continue;
        }

        float S[64];
        auto issue_q = [&](int first_acc) {
            wait_full(g);
            const uint32_t pg = sb + (g & 3) * (3 * PAGE);
            const uint64_t da = make_desc(pg + w * 8192, 16), db = make_desc(pg + 2 * PAGE, 8192);
            const uint64_t dab = make_desc(pg + PAGE + (1 - w) * 8192, 16);
            wg_fence();
#pragma unroll
            for (int q = 0; q < 4; q++) {
                wgmma_n128_ss(S, da + 2 * q, db + 128 * q, q ? 1 : first_acc);
                wgmma_n128_ss(O, dab + 2 * q, db + 128 * q, q ? 1 : first_acc);
            }
            wg_commit();
            g++;
        };
        auto issue_half = [&](float (&A)[64], uint32_t pg, uint32_t a_off) {
            const uint64_t da = make_desc(pg + a_off, 16), db = make_desc(pg + 2 * PAGE, 8192);
#pragma unroll
            for (int q = 0; q < 4; q++) wgmma_n128_ss(A, da + 2 * q, db + 128 * q, 1);
            wg_commit();
        };
        issue_q(0);
#pragma unroll 1
        for (int kb = 1; kb < DM / 64; kb++) {
            if (kb == DM / 64 - 3 && w == 1) bar_sync(4, 256);
            const bool defer = kb >= DM / 64 - 2;
            if (!defer) {
                issue_q(1);
            } else {
                wait_full(g);
                wg_fence();
                issue_half(S, sb + (g & 3) * (3 * PAGE), w * 8192);
                g++;
            }
            if (kb == DM / 64 - 2 && w == 0) bar_arrive(4, 256);
            wg_wait<1>();
            if (kb < DM / 64 - 1) release(g - 2);
            if (kb <= 8) {
                write_part(kb - 1);
                if (kb == 8) mark_done();
            }
        }
        uint32_t Q[32], Pm[32];
#pragma unroll
        for (int i = 0; i < 32; i++) Pm[i] = 0;
        float lim = (float)(v * 16 + (lane >> 2) - 8 * (lane & 3));
        l[0] = l[1] = 0.f;
        float mc[2] = {0.f, 0.f}, scale[2] = {0.f, 0.f}, sum[4];
        uint32_t kq = g * 8, vq = g * 8, ks = 0, vs = 0, ctl;
        int t = 0;
        reg_fence(Pm);
        asm volatile("" : "+f"(lim), "+f"(mc[0]), "+f"(mc[1]), "+f"(l[0]), "+f"(l[1]), "+f"(scale[0]), "+f"(scale[1]));
        asm volatile("" : "+r"(kq), "+r"(vq), "+r"(ks), "+r"(vs), "+r"(t));
        wg_wait<0>();
        reg_fence(S);
        reg_fence(O);
        PROF(2 + 2 * item, w);
        if (w == 0) PROF_GT(2 + 2 * item);

#pragma unroll
        for (int i = 0; i < 32; i++) Q[i] = pack_bf16(S[2 * i], S[2 * i + 1]);
        const uint32_t qpark = stg + lane * 16;
        constexpr int T = 17;
        uint32_t shifted = 0;
        uint32_t tick = 0;
        constexpr uint32_t SLOT = (2 * PAGE) >> 4;
        const uint32_t kdesc0 = (uint32_t)make_desc(sb, PAGE), vdesc0 = (uint32_t)make_desc(sb, 16);
        wait_full(g);
        do {
            bar_sync(2 + w, 256);
            wg_fence();
            issue_qk(S, Q, desc_hi | (kdesc0 + ks));
            wg_commit();
            ctl = __shfl_sync(~0u, ctl_tab, t);
            mbar_wait(sb + BAR_FULL + (vq & 56), (vq >> 6) & 1);
            uint32_t krel = empty_rel + (kq & 56), vrel = empty_rel + (vq & 56);
            const uint64_t vdesc = desc_hi | (vdesc0 + vs);
            if (ctl & (CTL_SWITCH | CTL_SKIPREL)) {
                if (ctl & CTL_SKIPREL) { release((kq >> 3) - 2); release((kq >> 3) + 1); }
                if (ctl & CTL_SWITCH) {
                    scale[0] = rcp_approx(quad_sum(l[0]));
                    scale[1] = rcp_approx(quad_sum(l[1]));
                    l[0] = l[1] = mc[0] = mc[1] = 0.f;
                    shifted = false;
                    pend = ptr_off(ctx_dst(item == 5, 0), chunk0);
                    asm volatile("" : "+l"(pend));
                }
            }
            const uint32_t kadv = (ctl >> 16) & 7, vadv = ctl >> 20;
            kq += kadv * 8; ks += kadv * SLOT; ks = ks >= 6 * SLOT ? ks - 6 * SLOT : ks;
            vq += vadv * 8; vs += vadv * SLOT; vs = vs >= 6 * SLOT ? vs - 6 * SLOT : vs;
            t++;
            uint32_t kbar = sb + BAR_FULL + (kq & 56), kpar = (kq >> 6) & 1;
            asm volatile("" : "+r"(krel), "+r"(vrel), "+r"(kbar), "+r"(kpar), "+r"(ks), "+r"(vs), "+r"(kq), "+r"(vq), "+r"(t));
            if (!(ctl & (CTL_START | CTL_PVHALF))) {
                wg_fence();
                issue_pv<0, 1>(O, Pm, vdesc, ctl & CTL_PVACC);
                wg_commit();
                issue_pv<1, 4>(O, Pm, vdesc, 1);
                wg_commit();
                issue_pv<4, 8>(O, Pm, vdesc, 1);
                wg_commit();
            } else if (ctl & CTL_PVHALF) {
                wg_fence();
                issue_pv<0, 1>(O, Pm, vdesc, ctl & CTL_PVACC);
                wg_commit();
                issue_pv<1, 4>(O, Pm, vdesc, 1);
                wg_commit();
                wg_commit();
            } else {
                wg_fence();
                issue_half(O, sb + 6 * PAGE, PAGE + (1 - w) * 8192);
                issue_half(O, sb + 9 * PAGE, PAGE + (1 - w) * 8192);
            }
            bar_arrive(3 - w, 256);
            auto scores_done = [&]() {
                sched_fence(tick, lane < 3);
                wg_wait<2>();
                reg_fence(S);
                if (lane < 3) mbar_arrive_cluster(krel);
            };
            auto load_q = [&]() {
#pragma unroll
                for (int i = 0; i < 8; i++) lds128(qpark + (i >> 2) * 8192 + (i & 3) * 512, Q[4 * i], Q[4 * i + 1], Q[4 * i + 2], Q[4 * i + 3]);
            };
            if ((ctl & (CTL_HALF | CTL_MASKHI | CTL_LOADQ)) || shifted) {
                scores_done();
                if (ctl & CTL_LOADQ) load_q();
                if (ctl & CTL_HALF) mask_half<0>(S, lim);
                if (ctl & CTL_MASKHI) mask_half<8>(S, lim);
                if (shifted) shift_rows(S, mc[0], mc[1]);
            } else {
                scores_done();
            }
            const bool kready = mbar_test(kbar, kpar);
            sum[0] = sum[1] = sum[2] = sum[3] = 0.f;
            float e[64];
#pragma unroll
            for (int i = 0; i < 16; i++) asm volatile("" : "+r"(Pm[i])::"memory");
            exp_stages<0, 16, 32, 4 + LAG>(S, e, Pm, sum, tick, lane < 3);
            auto pv_done = [&](bool rel) {
                sched_fence(tick, lane < 3);
                wg_wait<0>();
                reg_fence(O);
                if (rel && lane < 3) mbar_arrive_cluster(vrel);
#pragma unroll
                for (int i = 16; i < 32; i++) asm volatile("" : "+r"(Pm[i])::"memory");
            };
            const bool half = ctl & CTL_HALF, first = ctl & (CTL_START | CTL_SWITCH);
            float limit = SUM_HI;
            float a0 = 0.f, a1 = 0.f, ta = 0.f, tb = 0.f;
            auto low_check = [&](int k) {
                auto bfly = [](float x, int m) { float r; asm volatile("shfl.sync.bfly.b32 %0, %1, %2, 0x1f, 0xffffffff;" : "=f"(r) : "f"(x), "r"(m)); return r; };
                if (k == 16 + LAG) { a0 = sum[0] + sum[1]; a1 = sum[2] + sum[3]; asm volatile("" : "+f"(a0), "+f"(a1)); }
                if (k == 17 + LAG) { ta = bfly(a0, 1); tb = bfly(a1, 1); }
                if (k == 20 + LAG) { a0 += ta; a1 += tb; asm volatile("" : "+f"(a0), "+f"(a1)); }
                if (k == 21 + LAG) { ta = bfly(a0, 2); tb = bfly(a1, 2); }
                if (k == 24 + LAG) { if (!(fminf(a0 + ta, a1 + tb) >= SUM_LO)) limit = -1.f; asm volatile("" : "+f"(limit)); }
            };
            if (!(ctl & (CTL_HALF | CTL_SWITCH | CTL_START))) {
                pv_done(true);
                exp_stages<16, 32 + LAG, 32, -1>(S, e, Pm, sum, tick, lane < 3);
            } else if (half) {
                pv_done(!(ctl & CTL_START));
                exp_stages<16, 16 + LAG, 16, -1>(S, e, Pm, sum, tick, lane < 3);
                if (ctl & CTL_START) {
                    release(g - 2); release(g - 1);
#pragma unroll
                    for (int i = 0; i < 32; i++) Q[i] = pack_bf16(O[2 * i], O[2 * i + 1]);
                    if (!(fminf(quad_sum(sum[0] + sum[1]), quad_sum(sum[2] + sum[3])) >= SUM_LO)) limit = -1.f;
                }
            } else if (ctl & CTL_START) {
                pv_done(false);
                release(g - 2); release(g - 1);
                if (ctl & CTL_DIRECT) {
                    exp_stages<16, 32 + LAG, 32, -1>(S, e, Pm, sum, tick, lane < 3, [&](int k) {
                        low_check(k);
                        if (k < 32) {
#pragma unroll
                            for (int i = 2 * (k - 16); i < 2 * (k - 16) + 2; i++)
                                asm volatile("cvt.rn.bf16x2.f32 %0, %1, %2;" : "=r"(Q[i]) : "f"(O[2 * i + 1]), "f"(O[2 * i]));
                        }
                    });
                } else {
                    uint32_t u[32] = {};
                    exp_stages<16, 32 + LAG, 32, -1>(S, e, Pm, sum, tick, lane < 3, [&](int k) {
                        low_check(k);
                        if (k < 32) {
#pragma unroll
                            for (int i = 2 * (k - 16); i < 2 * (k - 16) + 2; i++)
                                asm volatile("cvt.rn.bf16x2.f32 %0, %1, %2;" : "=r"(u[i]) : "f"(O[2 * i + 1]), "f"(O[2 * i]));
                        }
                        const int i = (k - 18) >> 1;
                        if (k >= 18 && !(k & 1) && i < 8) sts128(qpark + (i >> 2) * 8192 + (i & 3) * 512, u[4 * i], u[4 * i + 1], u[4 * i + 2], u[4 * i + 3]);
                    });
                }
            } else {
                pv_done(true);
                uint8_t* d[2] = {pend, (uint8_t*)((uintptr_t)pend ^ 64)};
                uint32_t po[32] = {};
                exp_stages<16, 32 + LAG, 32, -1>(S, e, Pm, sum, tick, lane < 3, [&](int k) {
                    low_check(k);
                    const int q = (k - 18) >> 1;
                    if (k >= 19 && (k & 1) && q < 8)
                        __stcg(reinterpret_cast<uint4*>(d[(q >> 1) & 1] + (q >> 2) * PAGE + (q & 1) * 1024), make_uint4(po[4 * q], po[4 * q + 1], po[4 * q + 2], po[4 * q + 3]));
                    if (k >= 32) return;
                    const int i = (k - 16) >> 1, h = (k & 1) * 2;
                    const float sc = scale[i & 1];
#pragma unroll
                    for (int r = h; r < h + 2; r++) {
                        float x0, x1;
                        asm volatile("mul.f32 %0, %1, %2;" : "=f"(x0) : "f"(O[chunk_src(4 * i + r)]), "f"(sc));
                        asm volatile("mul.f32 %0, %1, %2;" : "=f"(x1) : "f"(O[chunk_src(4 * i + r) + 1]), "f"(sc));
                        asm volatile("cvt.rn.bf16x2.f32 %0, %1, %2;" : "=r"(po[4 * i + r]) : "f"(x1), "f"(x0));
                    }
                });
                mark_done();
            }
            sum[0] += sum[1]; sum[2] += sum[3];
            float chk = sum[0] + sum[2];
            const bool bad = !(chk <= limit);
            if (__any_sync(~0u, bad)) {
                if (half) {
#pragma unroll
                    for (int i = 32; i < 64; i++) S[i] = -INFINITY;
                }
                float d0 = fmaxf(S[0], S[1]), d1 = fmaxf(S[2], S[3]);
#pragma unroll
                for (int j = 1; j < 16; j++) {
                    d0 = fmaxf(d0, fmaxf(S[4 * j], S[4 * j + 1]));
                    d1 = fmaxf(d1, fmaxf(S[4 * j + 2], S[4 * j + 3]));
                }
                d0 = fmaxf(d0, __shfl_xor_sync(~0u, d0, 1));
                d1 = fmaxf(d1, __shfl_xor_sync(~0u, d1, 1));
                d0 = fmaxf(d0, __shfl_xor_sync(~0u, d0, 2));
                d1 = fmaxf(d1, __shfl_xor_sync(~0u, d1, 2));
                if (!first) {
                    d0 = fmaxf(d0, 0.f);
                    d1 = fmaxf(d1, 0.f);
                    const float a0 = ex2(-d0), a1 = ex2(-d1);
#pragma unroll
                    for (int j = 0; j < 16; j++) {
                        O[4 * j] *= a0; O[4 * j + 1] *= a0; O[4 * j + 2] *= a1; O[4 * j + 3] *= a1;
                    }
                    l[0] *= a0; l[1] *= a1;
                }
                mc[0] += d0; mc[1] += d1;
                shifted = true;
                shift_rows(S, d0, d1);
                sum[0] = sum[1] = sum[2] = sum[3] = 0.f;
                exp_part<0, 8>(S, Pm, sum);
                exp_part<8, 16>(S, Pm, sum);
                sum[0] += sum[1]; sum[2] += sum[3];
            }
            l[0] += sum[0]; l[1] += sum[2];
            if (!kready) mbar_wait(kbar, kpar);
        } while (t < T);
        asm volatile("" : "+r"(t));
        g += 36;
        if (t > T) asm volatile("st.shared.u32 [%0], %1;" ::"r"(sb + SM_PROF), "r"(tick) : "memory");
        const uint64_t vdesc = desc_hi | (vdesc0 + vs);
        wait_full(vq >> 3);
        if (ctl & CTL_HALF) {
            wg_fence();
            issue_pv<0, 4>(O, Pm, vdesc, !(ctl & CTL_SWITCH));
            wg_commit();
        } else {
            wg_fence();
            issue_pv<0, 4>(O, Pm, vdesc, !(ctl & CTL_SWITCH));
            issue_pv<4, 8>(O, Pm, vdesc, 1);
            wg_commit();
        }
        if (item == 5) break;
        finish_attention(0, g);
        PROF(3 + 2 * item, w);
        if (w == 0) PROF_GT(3 + 2 * item);
    }

    float acc[64];
    uint32_t slot = 0;
    const uint32_t da0 = (uint32_t)make_desc(sb + w * 8192, 16), db0 = (uint32_t)make_desc(sb + PAGE, 8192);
    uint32_t da = da0, db = db0, fbar = sb + BAR_FULL + (g & 7) * 8, fpar = (g >> 3) & 1, rel = 0;
    auto issue_out = [&](int first_acc) {
        mbar_wait(fbar, fpar);
        wg_fence();
#pragma unroll
        for (int q = 0; q < 4; q++) wgmma_n128_ss(acc, (desc_hi | da) + 2 * q, (desc_hi | db) + 128 * q, q ? 1 : first_acc);
        wg_commit();
        rel = empty_rel + ((g - 1) & 7) * 8;
        g++;
        slot = slot == SM_REGION - 2 * PAGE ? 0 : slot + 2 * PAGE;
        da = da0 + (slot >> 4); db = db0 + (slot >> 4);
        fbar = sb + BAR_FULL + (g & 7) * 8; fpar = (g >> 3) & 1;
        asm volatile("" : "+r"(da), "+r"(db), "+r"(fbar), "+r"(fpar), "+r"(rel), "+r"(slot), "+r"(g));
    };
    issue_out(0);
    finish_attention(1, g - 1);
    PROF(13, w);
    if (w == 0) PROF_GT(13);
    uint32_t xr[32], gr[32];
#pragma unroll
    for (int i = 0; i < 32; i++) gr[i] = 0;
#pragma unroll 1
    for (int kb = 1; kb < 64; kb++) {
        if (kb == 60 && w == 1) bar_sync(4, 256);
        issue_out(1);
        if (kb == 63 && w == 0) bar_arrive(4, 256);
        wg_wait<1>();
        if (kb < 60 && lane < 3) mbar_arrive_cluster(rel);
        if (kb <= 8 && !(kb & 1)) {
            store_part4(pend, (kb >> 1) - 1, pk);
            if (kb == 8) mark_done();
        }
        if (kb >= 28 && kb < 60 && (kb & 3) == 2 * w) {
            uint32_t u0, u1, u2, u3;
            const int s = (kb - 28) >> 2;
            mbar_wait(sb + BAR_G + w * 8, 0);
            ldmatrix_x4(slab_addr(stg, lane, s), u0, u1, u2, u3);
            set_quad(gr, s, pack_bf16(silu_f(bf_lo(u0)), silu_f(bf_hi(u0))), pack_bf16(silu_f(bf_lo(u1)), silu_f(bf_hi(u1))),
                     pack_bf16(silu_f(bf_lo(u2)), silu_f(bf_hi(u2))), pack_bf16(silu_f(bf_lo(u3)), silu_f(bf_hi(u3))));
        }
    }
    mbar_wait(fbar, fpar);
    const uint32_t xs = sb + slot + w * PAGE + v * 2048;
#pragma unroll
    for (int s = 0; s < 8; s++) ldmatrix_x4(slab_addr(xs, lane, s), xr[4 * s], xr[4 * s + 1], xr[4 * s + 2], xr[4 * s + 3]);
    wg_wait<0>();
    reg_fence(acc);
    PROF(14, w);
    if (w == 0) PROF_GT(14);
#pragma unroll
    for (int s = 0; s < 8; s++) {
        uint32_t o[4];
#pragma unroll
        for (int k = 0; k < 4; k++)
            o[k] = bf2_add(xr[4 * s + k], bf2_mul(pack_bf16(acc[8 * s + 2 * k], acc[8 * s + 2 * k + 1]), gr[4 * s + k]));
        stmatrix_x4(slab_addr(stg, lane, s), o[0], o[1], o[2], o[3]);
        if ((s & 3) == 3) {
            fence_async_smem();
            __syncwarp();
            const int orow = ((pair >> 1) & 7) * 256 + c * 128 + w * 64 + v * 16, ocol = (pair >> 4) * 256 + (pair & 1) * 128;
            if (lane == 0) tma_store_2d(m_out, ocol + (s >> 2) * 64, orow, stg + (s >> 2) * 8192);
        }
    }
    PROF(28, w);
    if (lane == 0) {
        bulk_commit();
        bulk_wait_read();
    }
    __syncwarp();
}

__global__ void __cluster_dims__(2, 1, 1) __launch_bounds__(384, 1)
fused_kernel(const __grid_constant__ CUtensorMap m_ckv, const __grid_constant__ CUtensorMap m_wuk,
             const __grid_constant__ CUtensorMap m_wuv, const __grid_constant__ CUtensorMap m_wq,
             const __grid_constant__ CUtensorMap m_wo, const __grid_constant__ CUtensorMap m_x,
             const __grid_constant__ CUtensorMap m_out, const __grid_constant__ CUtensorMap m_gate,
             const __grid_constant__ CUtensorMap m_up, const __grid_constant__ CUtensorMap m_down, const Params P) {
    extern __shared__ __align__(1024) uint8_t smem[];
    const uint32_t sb = __shfl_sync(~0u, smem_u32(smem), 0);
    const int tid = threadIdx.x;
    const int cl = blockIdx.x >> 1, c = blockIdx.x & 1;
    const int pair = cl >= 64 ? cl : cl < 4 ? cl * 16 + 15 : cl < 36 ? ((cl - 4) >> 3) * 16 + ((cl - 4) & 7)
                                                                    : ((cl - 36) / 7) * 16 + 8 + (cl - 36) % 7;
    const int warp = __shfl_sync(~0u, tid >> 5, 0), lane = tid & 31;
    auto init_barriers = [&](int i0, int i1) {
#pragma unroll
        for (int i = i0; i < i1; i++) mbar_init(sb + SM_BAR + i * 8, (i >> 3) == 1 ? 16 : i >= 25 ? 8 : 1);
        asm volatile("fence.mbarrier_init.release.cluster;" ::: "memory");
    };
    auto finish = [&]() {
        PROF(29, tid >> 7);
        if (tid == 0) atomicAdd(&g_sync.done, 1u);
    };
    if (pair >= NMAIN / 2) {
        if (tid == 256) init_barriers(0, 16);
        if (tid == 288) *reinterpret_cast<uint32_t*>(smem + PAUSE) = 0;
        __syncthreads();
        const unsigned epoch = __ldcg(&g_sync.done) / NCTA;
        if (warp < 8) ffn_cta(smem, sb, blockIdx.x - NMAIN, epoch, P.w_r);
        else if (tid == 256) ffn_producer(sb, blockIdx.x - NMAIN, epoch + 1, &m_gate, &m_up, &m_down);
        else if (tid == 288) ffn_pacer(sb, epoch + 1);
        __syncwarp();
        finish();
    } else if (warp < 8) {
        const uint32_t r0 = tid >> 3, ch = tid & 7, dst = sb + r0 * 128 + ((ch ^ (r0 & 7)) << 4);
        const uint32_t wo = r0 * 8192 + (pair & 15) * 256 + c * 128 + ch * 16;
        const uint8_t* sw[2] = {ptr_off(P.w_uk, wo), ptr_off(P.w_uv, wo)};
        const uint8_t* sc = ptr_off(P.c_kv, ((pair >> 4) * 512 + r0) * 1024 + ch * 16);
#pragma unroll
        for (int i = 0; i < 4; i++) cp_async16(dst + i * 4096, sw[i >> 1] + (i & 1) * 262144);
#pragma unroll
        for (int i = 0; i < 8; i++) cp_async16(dst + PAGE + i * 4096, sc + i * 32768);
        asm volatile("barrier.cluster.arrive.relaxed.aligned;" ::: "memory");
        asm volatile("setmaxnreg.inc.sync.aligned.u32 240;");
        consumer(sb, pair, c, &m_out, (const uint8_t*)P.x);
        finish();
    } else {
        asm volatile("setmaxnreg.dec.sync.aligned.u32 24;");
        auto load_w = [&](int kb) {
            tma_3d(sb + kb * (3 * PAGE), &m_wuk, 0, kb * 64, (pair & 15) * 2 + c, sb + BAR_FULL + kb * 8);
            tma_3d(sb + kb * (3 * PAGE) + 8192, &m_wuv, 0, kb * 64, (pair & 15) * 2 + c, sb + BAR_FULL + kb * 8);
        };
        if (tid == 256) {
            init_barriers(0, NBAR);
            prefetch_map(&m_ckv);
            prefetch_map(&m_wuv);
            mbar_arrive(sb + BAR_FULL);
#pragma unroll 1
            for (int kb = 1; kb < 4; kb++) {
                mbar_expect_tx(sb + BAR_FULL + kb * 8, 3 * PAGE);
                if (kb <= 1) load_w(kb);
            }
        }
        PROF(18, 0);
        __syncwarp();
        cluster_sync();
        PROF(22, 0);
        if (tid == 256) {
#pragma unroll 1
            for (int kb = 1; kb < 4; kb++) {
                if (kb > 1) load_w(kb);
                tma_3d_mc(sb + kb * (3 * PAGE) + (1 + c) * PAGE, &m_ckv, 0, (pair >> 4) * 512 + c * 128, kb, sb + BAR_FULL + kb * 8);
            }
        }
        __syncwarp();
        PROF(19, 0);
        if (warp == 10) {
            sync_helper(sb, lane, pair, c);
        } else if (warp & 1) {
            fetch_helper(P.c_kv, sb, (warp >> 1) & 1, lane, pair, c);
        } else {
            producer(P, sb, pair, c, &m_ckv, &m_wuk, &m_wuv, &m_wq, &m_wo, &m_x, &m_out);
        }
    }
}

typedef CUresult (*EncodeFn)(CUtensorMap*, CUtensorMapDataType, cuuint32_t, void*, const cuuint64_t*, const cuuint64_t*,
                             const cuuint32_t*, const cuuint32_t*, CUtensorMapInterleave, CUtensorMapSwizzle,
                             CUtensorMapL2promotion, CUtensorMapFloatOOBfill);

void make_map_2d(EncodeFn fn, CUtensorMap* m, const void* ptr, int rows, int cols, int box_rows) {
    cuuint64_t dims[2] = {(cuuint64_t)cols, (cuuint64_t)rows};
    cuuint64_t strides[1] = {(cuuint64_t)cols * 2};
    cuuint32_t box[2] = {64, (cuuint32_t)box_rows};
    cuuint32_t es[2] = {1, 1};
    fn(m, CU_TENSOR_MAP_DATA_TYPE_BFLOAT16, 2, const_cast<void*>(ptr), dims, strides, box, es, CU_TENSOR_MAP_INTERLEAVE_NONE,
       CU_TENSOR_MAP_SWIZZLE_128B, CU_TENSOR_MAP_L2_PROMOTION_L2_256B, CU_TENSOR_MAP_FLOAT_OOB_FILL_NONE);
}
void make_map_w(EncodeFn fn, CUtensorMap* m, const void* ptr, int rows, int cols, int blocks, int box_rows) {
    cuuint64_t dims[3] = {64, (cuuint64_t)rows, (cuuint64_t)cols / 64};
    cuuint64_t strides[2] = {(cuuint64_t)cols * 2, 128};
    cuuint32_t box[3] = {64, (cuuint32_t)box_rows, (cuuint32_t)blocks};
    cuuint32_t es[3] = {1, 1, 1};
    fn(m, CU_TENSOR_MAP_DATA_TYPE_BFLOAT16, 3, const_cast<void*>(ptr), dims, strides, box, es, CU_TENSOR_MAP_INTERLEAVE_NONE,
       CU_TENSOR_MAP_SWIZZLE_128B, CU_TENSOR_MAP_L2_PROMOTION_L2_128B, CU_TENSOR_MAP_FLOAT_OOB_FILL_NONE);
}

void make_map_wo(EncodeFn fn, CUtensorMap* m, const void* ptr) {
    cuuint64_t dims[5] = {DM, 2, 4, 4, NH * 128 / 32};
    cuuint64_t strides[4] = {DM * 2, 8 * DM * 2, 2 * DM * 2, 32 * DM * 2};
    cuuint32_t box[5] = {64, 2, 4, 4, 2};
    cuuint32_t es[5] = {1, 1, 1, 1, 1};
    fn(m, CU_TENSOR_MAP_DATA_TYPE_BFLOAT16, 5, const_cast<void*>(ptr), dims, strides, box, es, CU_TENSOR_MAP_INTERLEAVE_NONE,
       CU_TENSOR_MAP_SWIZZLE_128B, CU_TENSOR_MAP_L2_PROMOTION_L2_256B, CU_TENSOR_MAP_FLOAT_OOB_FILL_NONE);
}

}

extern "C" void kernel_launch(void* const* d_in, const int* in_sizes, int n_in, void* d_out, int out_size) {
    static EncodeFn fn = nullptr;
    if (!fn) {
        void* f = nullptr;
        cudaDriverEntryPointQueryResult qr;
        cudaGetDriverEntryPoint("cuTensorMapEncodeTiled", &f, cudaEnableDefault, &qr);
        fn = (EncodeFn)f;
        cudaFuncSetAttribute(fused_kernel, cudaFuncAttributeMaxDynamicSharedMemorySize, SMEM_BYTES);
    }
    CUtensorMap m_ckv, m_wuk, m_wuv, m_wq, m_wo, m_x, m_out, m_gate, m_up, m_down;
    make_map_w(fn, &m_gate, d_in[8], DM, FF, FS / 64, 16);
    make_map_w(fn, &m_up, d_in[9], DM, FF, FS / 64, 16);
    make_map_w(fn, &m_down, d_in[10], FF, DM, DM / 64, 16);
    make_map_w(fn, &m_ckv, d_in[1], SEQ, DC, 1, 128);
    make_map_w(fn, &m_wq, d_in[2], DM, NH * 128, 1, 64);
    make_map_w(fn, &m_wuk, d_in[3], DC, NH * 128, 1, 64);
    make_map_w(fn, &m_wuv, d_in[4], DC, NH * 128, 1, 64);
    make_map_wo(fn, &m_wo, d_in[5]);
    make_map_w(fn, &m_x, d_in[0], SEQ, DM, 2, 64);
    make_map_2d(fn, &m_out, d_out, SEQ, DM, 16);
    Params P;
    P.x = (const __nv_bfloat16*)d_in[0];
    P.w_r = (const __nv_bfloat16*)d_in[7];
    P.c_kv = (const uint8_t*)d_in[1];
    P.w_uk = (const uint8_t*)d_in[3];
    P.w_uv = (const uint8_t*)d_in[4];
    P.w_o = (const uint8_t*)d_in[5];
    fused_kernel<<<NCTA, 384, SMEM_BYTES>>>(m_ckv, m_wuk, m_wuv, m_wq, m_wo, m_x, m_out, m_gate, m_up, m_down, P);
}
```

```cpp
#include <cuda_runtime.h>
#include <cuda_bf16.h>
#include <cuda.h>
#include <stdint.h>

namespace {

constexpr int SEQ = 2048, DM = 1024, NH = 32, DC = 512, FF = 3584;
constexpr int PAGE = 16384;
constexpr int NRING = 12;
constexpr int NCTA = 132, NMAIN = 128;
constexpr uint32_t SM_REGION = NRING * PAGE;
constexpr uint32_t SM_BAR = (NRING + 2) * PAGE;
constexpr uint32_t BAR_FULL = SM_BAR, BAR_EMPTY = SM_BAR + 64;
constexpr uint32_t BAR_DEP = SM_BAR + 128;
constexpr uint32_t BAR_G = SM_BAR + 184;
constexpr uint32_t BAR_DONE = SM_BAR + 200;
constexpr uint32_t BAR_EMPTYL = SM_BAR + 216;
constexpr int NBAR = 35;
constexpr uint32_t SM_PROF = SM_BAR + 320;
constexpr int SMEM_BYTES = SM_PROF + 512;
constexpr uint32_t SPIN_LIMIT = 1u << 16;
constexpr uint32_t POLL_MASK = 7;

struct SyncBlock {
    unsigned done;       unsigned pad0[31];
    unsigned ln;         unsigned pad1[31];
    unsigned router;     unsigned pad4[31];
    unsigned ffn_ticket; unsigned pad2[31];
    unsigned ffn_done;   unsigned pad3[31];
    unsigned kv[NH * 8];
    unsigned kvfree[16 * 8];
    unsigned ctx[32 * NH];
};

__device__ __align__(1024) uint8_t g_xn[8 * 16 * 4 * 8192];
__device__ __align__(1024) uint8_t g_kv[16 * 16 * 65536];
__device__ __align__(1024) uint8_t g_ctx[16 * 64 * 16384];
__device__ __align__(16) uint4 g_routed[2 * 128];
__device__ int g_sel[2];
__device__ __align__(16) float g_r[SEQ];
__device__ __align__(16) float g_ypart[4 * 2 * DM];
__device__ SyncBlock g_sync;

__device__ __forceinline__ uint32_t smem_u32(const void* p) { return (uint32_t)__cvta_generic_to_shared(p); }

__device__ __forceinline__ void mbar_init(uint32_t bar, uint32_t count) {
    asm volatile("mbarrier.init.shared::cta.b64 [%0], %1;" ::"r"(bar), "r"(count) : "memory");
}
#define MBAR_WAIT_ASM(HINT, LIMIT)                                                                  \
    asm volatile("{\n.reg .pred p;\n.reg .u32 n;\nmov.u32 n, 0;\n"                                  \
                 "WAIT_LOOP:\n"                                                                     \
                 "mbarrier.try_wait.parity.shared::cta.b64 p, [%0], %1" HINT ";\n"                  \
                 "@p bra WAIT_DONE;\n"                                                              \
                 "add.u32 n, n, 1;\n"                                                               \
                 "setp.lt.u32 p, n, " LIMIT ";\n"                                                   \
                 "@p bra WAIT_LOOP;\n"                                                              \
                 "WAIT_DONE:\n}\n" ::"r"(bar), "r"(parity) : "memory")
__device__ __forceinline__ void mbar_wait(uint32_t bar, uint32_t parity) { MBAR_WAIT_ASM("", "131072"); }
__device__ __forceinline__ void mbar_sleep(uint32_t bar, uint32_t parity) { MBAR_WAIT_ASM(", 2000", "8192"); }
__device__ __forceinline__ bool mbar_try(uint32_t bar, uint32_t parity) {
    uint32_t ok;
    asm volatile("{\n.reg .pred p;\nmbarrier.try_wait.parity.shared::cta.b64 p, [%1], %2;\nselp.u32 %0, 1, 0, p;\n}\n"
                 : "=r"(ok) : "r"(bar), "r"(parity) : "memory");
    return ok;
}
__device__ __forceinline__ bool mbar_test(uint32_t bar, uint32_t parity) {
    uint32_t ok;
    asm volatile("{\n.reg .pred p;\nmbarrier.test_wait.parity.shared::cta.b64 p, [%1], %2;\nselp.u32 %0, 1, 0, p;\n}\n"
                 : "=r"(ok) : "r"(bar), "r"(parity) : "memory");
    return ok;
}
__device__ __forceinline__ bool elect_one() {
    uint32_t ok;
    asm volatile("{\n.reg .pred p;\nelect.sync _|p, 0xffffffff;\nselp.u32 %0, 1, 0, p;\n}\n" : "=r"(ok));
    return ok;
}
__device__ __forceinline__ void mbar_arrive(uint32_t bar) {
    asm volatile("mbarrier.arrive.shared::cta.b64 _, [%0];" ::"r"(bar) : "memory");
}
__device__ __forceinline__ void mbar_expect_tx(uint32_t bar, uint32_t bytes) {
    asm volatile("mbarrier.arrive.expect_tx.shared::cta.b64 _, [%0], %1;" ::"r"(bar), "r"(bytes) : "memory");
}
__device__ __forceinline__ void mbar_arrive_cluster(uint32_t cluster_addr) {
    asm volatile("mbarrier.arrive.shared::cluster.b64 _, [%0];" ::"r"(cluster_addr) : "memory");
}
__device__ __forceinline__ uint32_t mapa(uint32_t addr, uint32_t rank) {
    uint32_t r;
    asm("mapa.shared::cluster.u32 %0, %1, %2;" : "=r"(r) : "r"(addr), "r"(rank));
    return r;
}
__device__ __forceinline__ void tma_3d(uint32_t dst, const CUtensorMap* m, int c0, int c1, int c2, uint32_t bar) {
    asm volatile("cp.async.bulk.tensor.3d.shared::cluster.global.mbarrier::complete_tx::bytes [%0], [%1, {%3, %4, %5}], [%2];"
                 ::"r"(dst), "l"(m), "r"(bar), "r"(c0), "r"(c1), "r"(c2) : "memory");
}
__device__ __forceinline__ void tma_3d_hint(uint32_t dst, const CUtensorMap* m, int c0, int c1, int c2, uint32_t bar, uint64_t pol) {
    asm volatile("cp.async.bulk.tensor.3d.shared::cluster.global.mbarrier::complete_tx::bytes.L2::cache_hint [%0], [%1, {%3, %4, %5}], [%2], %6;"
                 ::"r"(dst), "l"(m), "r"(bar), "r"(c0), "r"(c1), "r"(c2), "l"(pol) : "memory");
}
__device__ __forceinline__ void tma_3d_mc(uint32_t dst, const CUtensorMap* m, int c0, int c1, int c2, uint32_t bar) {
    asm volatile("cp.async.bulk.tensor.3d.shared::cluster.global.mbarrier::complete_tx::bytes.multicast::cluster [%0], [%1, {%3, %4, %5}], [%2], %6;"
                 ::"r"(dst), "l"(m), "r"(bar), "r"(c0), "r"(c1), "r"(c2), "h"((uint16_t)3) : "memory");
}
__device__ __forceinline__ void tma_5d_mc(uint32_t dst, const CUtensorMap* m, int c0, int c4, uint32_t bar) {
    asm volatile("cp.async.bulk.tensor.5d.shared::cluster.global.mbarrier::complete_tx::bytes.multicast::cluster [%0], [%1, {%3, 0, 0, 0, %4}], [%2], %5;"
                 ::"r"(dst), "l"(m), "r"(bar), "r"(c0), "r"(c4), "h"((uint16_t)3) : "memory");
}
__device__ __forceinline__ void bulk_load(uint32_t dst, const void* src, uint32_t bytes, uint32_t bar) {
    asm volatile("cp.async.bulk.shared::cluster.global.mbarrier::complete_tx::bytes [%0], [%1], %2, [%3];"
                 ::"r"(dst), "l"(src), "r"(bytes), "r"(bar) : "memory");
}
__device__ __forceinline__ void cp_async16(uint32_t dst, const void* src) {
    asm volatile("cp.async.cg.shared.global [%0], [%1], 16;" ::"r"(dst), "l"(src) : "memory");
}
__device__ __forceinline__ void bulk_load_mc(uint32_t dst, const void* src, uint32_t bytes, uint32_t bar) {
    asm volatile("cp.async.bulk.shared::cluster.global.mbarrier::complete_tx::bytes.multicast::cluster [%0], [%1], %2, [%3], %4;"
                 ::"r"(dst), "l"(src), "r"(bytes), "r"(bar), "h"((uint16_t)3) : "memory");
}
__device__ __forceinline__ void tma_store_2d(const CUtensorMap* m, int c0, int c1, uint32_t src) {
    asm volatile("cp.async.bulk.tensor.2d.global.shared::cta.bulk_group [%0, {%2, %3}], [%1];"
                 ::"l"(m), "r"(src), "r"(c0), "r"(c1) : "memory");
}
__device__ __forceinline__ void bulk_commit() { asm volatile("cp.async.bulk.commit_group;" ::: "memory"); }
__device__ __forceinline__ void bulk_wait_read() { asm volatile("cp.async.bulk.wait_group.read 0;" ::: "memory"); }
__device__ __forceinline__ void fence_async_smem() { asm volatile("fence.proxy.async.shared::cta;" ::: "memory"); }
__device__ __forceinline__ void prefetch_map(const CUtensorMap* m) {
    asm volatile("prefetch.tensormap [%0];" ::"l"(m) : "memory");
}
__device__ __forceinline__ void red_release(unsigned* p) {
    asm volatile("red.release.gpu.global.add.u32 [%0], 1;" ::"l"(p) : "memory");
}
__device__ __forceinline__ unsigned ld_relaxed(const unsigned* p) {
    unsigned v;
    asm volatile("ld.relaxed.gpu.global.u32 %0, [%1];" : "=r"(v) : "l"(p) : "memory");
    return v;
}
__device__ __forceinline__ void wait_counter(const unsigned* p, unsigned target, unsigned ns = 100) {
    for (uint32_t n = 0; (int)(ld_relaxed(p) - target) < 0 && n < SPIN_LIMIT; n++) __nanosleep(ns);
    asm volatile("fence.acquire.gpu;" ::: "memory");
    asm volatile("fence.proxy.async.global;" ::: "memory");
}
__device__ __forceinline__ void bar_sync(int id, int n) { asm volatile("bar.sync %0, %1;" ::"r"(id), "r"(n) : "memory"); }
__device__ __forceinline__ void bar_arrive(int id, int n) { asm volatile("bar.arrive %0, %1;" ::"r"(id), "r"(n) : "memory"); }
__device__ __forceinline__ void cluster_sync() {
    asm volatile("barrier.cluster.arrive.relaxed.aligned;\nbarrier.cluster.wait.aligned;" ::: "memory");
}
__device__ __forceinline__ void wg_fence() { asm volatile("wgmma.fence.sync.aligned;" ::: "memory"); }
__device__ __forceinline__ void wg_commit() { asm volatile("wgmma.commit_group.sync.aligned;" ::: "memory"); }
template <int N> __device__ __forceinline__ void wg_wait() { asm volatile("wgmma.wait_group.sync.aligned %0;" ::"n"(N) : "memory"); }
template <int N> __device__ __forceinline__ void reg_fence(float (&a)[N]) {
#pragma unroll
    for (int i = 0; i < N; i++) asm volatile("" : "+f"(a[i])::"memory");
}
template <int N> __device__ __forceinline__ void reg_fence(uint32_t (&a)[N]) {
#pragma unroll
    for (int i = 0; i < N; i++) asm volatile("" : "+r"(a[i])::"memory");
}
__device__ __forceinline__ uint32_t pack_bf16(float lo, float hi) {
    uint32_t r;
    asm("cvt.rn.bf16x2.f32 %0, %1, %2;" : "=r"(r) : "f"(hi), "f"(lo));
    return r;
}
__device__ __forceinline__ float bf_lo(uint32_t v) { return __uint_as_float(v << 16); }
__device__ __forceinline__ float bf_hi(uint32_t v) { return __uint_as_float(v & 0xffff0000u); }
__device__ __forceinline__ float bf_round(float v) { return __bfloat162float(__float2bfloat16_rn(v)); }
__device__ __forceinline__ float ex2(float v) {
    float r;
    asm("ex2.approx.ftz.f32 %0, %1;" : "=f"(r) : "f"(v));
    return r;
}
__device__ __forceinline__ float sqrt_approx(float v) {
    float r;
    asm("sqrt.approx.ftz.f32 %0, %1;" : "=f"(r) : "f"(v));
    return r;
}
__device__ __forceinline__ float rcp_approx(float v) {
    float r;
    asm("rcp.approx.ftz.f32 %0, %1;" : "=f"(r) : "f"(v));
    return r;
}
__device__ __forceinline__ float silu_f(float v) { return v * rcp_approx(1.0f + ex2(v * -1.4426950408889634f)); }
__device__ __forceinline__ void stmatrix_x4(uint32_t addr, uint32_t r0, uint32_t r1, uint32_t r2, uint32_t r3) {
    asm volatile("stmatrix.sync.aligned.m8n8.x4.shared.b16 [%0], {%1, %2, %3, %4};"
                 ::"r"(addr), "r"(r0), "r"(r1), "r"(r2), "r"(r3) : "memory");
}
__device__ __forceinline__ void sts128(uint32_t addr, uint32_t r0, uint32_t r1, uint32_t r2, uint32_t r3) {
    asm volatile("st.shared.v4.b32 [%0], {%1, %2, %3, %4};" ::"r"(addr), "r"(r0), "r"(r1), "r"(r2), "r"(r3) : "memory");
}
__device__ __forceinline__ void lds128(uint32_t addr, uint32_t& r0, uint32_t& r1, uint32_t& r2, uint32_t& r3) {
    asm volatile("ld.shared.v4.b32 {%0, %1, %2, %3}, [%4];" : "=r"(r0), "=r"(r1), "=r"(r2), "=r"(r3) : "r"(addr) : "memory");
}
__device__ __forceinline__ void ldmatrix_x4(uint32_t addr, uint32_t& r0, uint32_t& r1, uint32_t& r2, uint32_t& r3) {
    asm volatile("ldmatrix.sync.aligned.m8n8.x4.shared.b16 {%0, %1, %2, %3}, [%4];"
                 : "=r"(r0), "=r"(r1), "=r"(r2), "=r"(r3) : "r"(addr) : "memory");
}
__device__ __forceinline__ uint32_t bf2_mul(uint32_t a, uint32_t b) {
    uint32_t r;
    asm("mul.rn.bf16x2 %0, %1, %2;" : "=r"(r) : "r"(a), "r"(b));
    return r;
}
__device__ __forceinline__ uint32_t bf2_add(uint32_t a, uint32_t b) {
    uint32_t r;
    asm("add.rn.bf16x2 %0, %1, %2;" : "=r"(r) : "r"(a), "r"(b));
    return r;
}
__device__ __forceinline__ uint64_t policy_evict_first() {
    uint64_t p;
    asm("createpolicy.fractional.L2::evict_first.b64 %0, 1.0;" : "=l"(p));
    return p;
}

__device__ __forceinline__ uint64_t make_desc(uint32_t addr, uint32_t lbo_bytes) {
    return (uint64_t)((addr & 0x3FFFF) >> 4) | ((uint64_t)(lbo_bytes >> 4) << 16) | ((uint64_t)(1024 >> 4) << 32) | (1ull << 62);
}

__device__ __forceinline__ void wgmma_n256_ss(float (&d)[128], uint64_t da, uint64_t db, int acc) {
    asm volatile(
        "{\n.reg .pred p;\nsetp.ne.b32 p, %130, 0;\n"
        "wgmma.mma_async.sync.aligned.m64n256k16.f32.bf16.bf16 {"
        "%0, %1, %2, %3, %4, %5, %6, %7, %8, %9, %10, %11, %12, %13, %14, %15, "
        "%16, %17, %18, %19, %20, %21, %22, %23, %24, %25, %26, %27, %28, %29, %30, %31, "
        "%32, %33, %34, %35, %36, %37, %38, %39, %40, %41, %42, %43, %44, %45, %46, %47, "
        "%48, %49, %50, %51, %52, %53, %54, %55, %56, %57, %58, %59, %60, %61, %62, %63, "
        "%64, %65, %66, %67, %68, %69, %70, %71, %72, %73, %74, %75, %76, %77, %78, %79, "
        "%80, %81, %82, %83, %84, %85, %86, %87, %88, %89, %90, %91, %92, %93, %94, %95, "
        "%96, %97, %98, %99, %100, %101, %102, %103, %104, %105, %106, %107, %108, %109, %110, %111, "
        "%112, %113, %114, %115, %116, %117, %118, %119, %120, %121, %122, %123, %124, %125, %126, %127"
        "}, %128, %129, p, 1, 1, 1, 0;\n}\n"
        :
        "+f"(d[0]), "+f"(d[1]), "+f"(d[2]), "+f"(d[3]), "+f"(d[4]), "+f"(d[5]), "+f"(d[6]), "+f"(d[7]),
        "+f"(d[8]), "+f"(d[9]), "+f"(d[10]), "+f"(d[11]), "+f"(d[12]), "+f"(d[13]), "+f"(d[14]), "+f"(d[15]),
        "+f"(d[16]), "+f"(d[17]), "+f"(d[18]), "+f"(d[19]), "+f"(d[20]), "+f"(d[21]), "+f"(d[22]), "+f"(d[23]),
        "+f"(d[24]), "+f"(d[25]), "+f"(d[26]), "+f"(d[27]), "+f"(d[28]), "+f"(d[29]), "+f"(d[30]), "+f"(d[31]),
        "+f"(d[32]), "+f"(d[33]), "+f"(d[34]), "+f"(d[35]), "+f"(d[36]), "+f"(d[37]), "+f"(d[38]), "+f"(d[39]),
        "+f"(d[40]), "+f"(d[41]), "+f"(d[42]), "+f"(d[43]), "+f"(d[44]), "+f"(d[45]), "+f"(d[46]), "+f"(d[47]),
        "+f"(d[48]), "+f"(d[49]), "+f"(d[50]), "+f"(d[51]), "+f"(d[52]), "+f"(d[53]), "+f"(d[54]), "+f"(d[55]),
        "+f"(d[56]), "+f"(d[57]), "+f"(d[58]), "+f"(d[59]), "+f"(d[60]), "+f"(d[61]), "+f"(d[62]), "+f"(d[63]),
        "+f"(d[64]), "+f"(d[65]), "+f"(d[66]), "+f"(d[67]), "+f"(d[68]), "+f"(d[69]), "+f"(d[70]), "+f"(d[71]),
        "+f"(d[72]), "+f"(d[73]), "+f"(d[74]), "+f"(d[75]), "+f"(d[76]), "+f"(d[77]), "+f"(d[78]), "+f"(d[79]),
        "+f"(d[80]), "+f"(d[81]), "+f"(d[82]), "+f"(d[83]), "+f"(d[84]), "+f"(d[85]), "+f"(d[86]), "+f"(d[87]),
        "+f"(d[88]), "+f"(d[89]), "+f"(d[90]), "+f"(d[91]), "+f"(d[92]), "+f"(d[93]), "+f"(d[94]), "+f"(d[95]),
        "+f"(d[96]), "+f"(d[97]), "+f"(d[98]), "+f"(d[99]), "+f"(d[100]), "+f"(d[101]), "+f"(d[102]), "+f"(d[103]),
        "+f"(d[104]), "+f"(d[105]), "+f"(d[106]), "+f"(d[107]), "+f"(d[108]), "+f"(d[109]), "+f"(d[110]), "+f"(d[111]),
        "+f"(d[112]), "+f"(d[113]), "+f"(d[114]), "+f"(d[115]), "+f"(d[116]), "+f"(d[117]), "+f"(d[118]), "+f"(d[119]),
        "+f"(d[120]), "+f"(d[121]), "+f"(d[122]), "+f"(d[123]), "+f"(d[124]), "+f"(d[125]), "+f"(d[126]), "+f"(d[127])
        : "l"(da), "l"(db), "r"(acc));
}

template <int TB>
__device__ __forceinline__ void wgmma_n128_rs(float (&d)[64], uint32_t a0, uint32_t a1, uint32_t a2, uint32_t a3, uint64_t db, int acc) {
    asm volatile(
        "{\n.reg .pred p;\nsetp.ne.b32 p, %69, 0;\n"
        "wgmma.mma_async.sync.aligned.m64n128k16.f32.bf16.bf16 {"
        "%0, %1, %2, %3, %4, %5, %6, %7, %8, %9, %10, %11, %12, %13, %14, %15, "
        "%16, %17, %18, %19, %20, %21, %22, %23, %24, %25, %26, %27, %28, %29, %30, %31, "
        "%32, %33, %34, %35, %36, %37, %38, %39, %40, %41, %42, %43, %44, %45, %46, %47, "
        "%48, %49, %50, %51, %52, %53, %54, %55, %56, %57, %58, %59, %60, %61, %62, %63"
        "}, {%64, %65, %66, %67}, %68, p, 1, 1, %70;\n}\n"
        :
        "+f"(d[0]), "+f"(d[1]), "+f"(d[2]), "+f"(d[3]), "+f"(d[4]), "+f"(d[5]), "+f"(d[6]), "+f"(d[7]),
        "+f"(d[8]), "+f"(d[9]), "+f"(d[10]), "+f"(d[11]), "+f"(d[12]), "+f"(d[13]), "+f"(d[14]), "+f"(d[15]),
        "+f"(d[16]), "+f"(d[17]), "+f"(d[18]), "+f"(d[19]), "+f"(d[20]), "+f"(d[21]), "+f"(d[22]), "+f"(d[23]),
        "+f"(d[24]), "+f"(d[25]), "+f"(d[26]), "+f"(d[27]), "+f"(d[28]), "+f"(d[29]), "+f"(d[30]), "+f"(d[31]),
        "+f"(d[32]), "+f"(d[33]), "+f"(d[34]), "+f"(d[35]), "+f"(d[36]), "+f"(d[37]), "+f"(d[38]), "+f"(d[39]),
        "+f"(d[40]), "+f"(d[41]), "+f"(d[42]), "+f"(d[43]), "+f"(d[44]), "+f"(d[45]), "+f"(d[46]), "+f"(d[47]),
        "+f"(d[48]), "+f"(d[49]), "+f"(d[50]), "+f"(d[51]), "+f"(d[52]), "+f"(d[53]), "+f"(d[54]), "+f"(d[55]),
        "+f"(d[56]), "+f"(d[57]), "+f"(d[58]), "+f"(d[59]), "+f"(d[60]), "+f"(d[61]), "+f"(d[62]), "+f"(d[63])
        : "r"(a0), "r"(a1), "r"(a2), "r"(a3), "l"(db), "r"(acc), "n"(TB));
}

__device__ __forceinline__ void wgmma_n128_ss(float* d, uint64_t da, uint64_t db, int acc) {
    asm volatile(
        "{\n.reg .pred p;\nsetp.ne.b32 p, %66, 0;\n"
        "wgmma.mma_async.sync.aligned.m64n128k16.f32.bf16.bf16 {"
        "%0, %1, %2, %3, %4, %5, %6, %7, %8, %9, %10, %11, %12, %13, %14, %15, "
        "%16, %17, %18, %19, %20, %21, %22, %23, %24, %25, %26, %27, %28, %29, %30, %31, "
        "%32, %33, %34, %35, %36, %37, %38, %39, %40, %41, %42, %43, %44, %45, %46, %47, "
        "%48, %49, %50, %51, %52, %53, %54, %55, %56, %57, %58, %59, %60, %61, %62, %63"
        "}, %64, %65, p, 1, 1, 0, 1;\n}\n"
        :
        "+f"(d[0]), "+f"(d[1]), "+f"(d[2]), "+f"(d[3]), "+f"(d[4]), "+f"(d[5]), "+f"(d[6]), "+f"(d[7]),
        "+f"(d[8]), "+f"(d[9]), "+f"(d[10]), "+f"(d[11]), "+f"(d[12]), "+f"(d[13]), "+f"(d[14]), "+f"(d[15]),
        "+f"(d[16]), "+f"(d[17]), "+f"(d[18]), "+f"(d[19]), "+f"(d[20]), "+f"(d[21]), "+f"(d[22]), "+f"(d[23]),
        "+f"(d[24]), "+f"(d[25]), "+f"(d[26]), "+f"(d[27]), "+f"(d[28]), "+f"(d[29]), "+f"(d[30]), "+f"(d[31]),
        "+f"(d[32]), "+f"(d[33]), "+f"(d[34]), "+f"(d[35]), "+f"(d[36]), "+f"(d[37]), "+f"(d[38]), "+f"(d[39]),
        "+f"(d[40]), "+f"(d[41]), "+f"(d[42]), "+f"(d[43]), "+f"(d[44]), "+f"(d[45]), "+f"(d[46]), "+f"(d[47]),
        "+f"(d[48]), "+f"(d[49]), "+f"(d[50]), "+f"(d[51]), "+f"(d[52]), "+f"(d[53]), "+f"(d[54]), "+f"(d[55]),
        "+f"(d[56]), "+f"(d[57]), "+f"(d[58]), "+f"(d[59]), "+f"(d[60]), "+f"(d[61]), "+f"(d[62]), "+f"(d[63])
        : "l"(da), "l"(db), "r"(acc));
}

__device__ __forceinline__ void wgmma_n8_ta(float* d, uint64_t da, uint64_t db) {
    asm volatile("wgmma.mma_async.sync.aligned.m64n8k16.f32.bf16.bf16 {%0, %1, %2, %3}, %4, %5, 1, 1, 1, 1, 0;\n"
                 : "+f"(d[0]), "+f"(d[1]), "+f"(d[2]), "+f"(d[3]) : "l"(da), "l"(db));
}

__device__ __forceinline__ void wgmma_n8(float* d, uint64_t da, uint64_t db) {
    asm volatile("wgmma.mma_async.sync.aligned.m64n8k16.f32.bf16.bf16 {%0, %1, %2, %3}, %4, %5, 1, 1, 1, 0, 0;\n"
                 : "+f"(d[0]), "+f"(d[1]), "+f"(d[2]), "+f"(d[3]) : "l"(da), "l"(db));
}

#define PROF(slot, role)
#undef PROF_GT
#define PROF_GT(slot)

struct Params {
    const __nv_bfloat16* x;
    const __nv_bfloat16* w_r;
    const uint8_t *c_kv, *w_uk, *w_uv, *w_o;
};
__device__ __forceinline__ void st16cs(uint4* p, uint4 v) {
    asm volatile("st.global.cs.v4.u32 [%0], {%1, %2, %3, %4};" ::"l"(p), "r"(v.x), "r"(v.y), "r"(v.z), "r"(v.w) : "memory");
}
__device__ __forceinline__ void lsu_prefetch(const void* p) { asm volatile("prefetch.global.L2 [%0];" ::"l"(p) : "memory"); }

template <typename T>
__device__ __forceinline__ T* ptr_off(T* base, uint32_t off) {
    uint32_t lo, hi;
    asm("mov.b64 {%0, %1}, %2;" : "=r"(lo), "=r"(hi) : "l"(base));
    asm("add.cc.u32 %0, %0, %2;\naddc.u32 %1, %1, 0;" : "+r"(lo), "+r"(hi) : "r"(off));
    T* r;
    asm("mov.b64 %0, {%1, %2};" : "=l"(r) : "r"(lo), "r"(hi));
    return r;
}
__device__ __forceinline__ int attn_rowblock(int pair, int seg) {
    int j = pair & 3, hl = pair >> 2;
    return (((hl & 1) | (j == 0)) ^ seg) ? j : 7 - j;
}
__device__ __forceinline__ int diag_place(int n, int i) {
    return (n >> 1) - 1 + (n < 6 ? i : 2 * i);
}
__device__ __forceinline__ int outproj_head(int i, int ib) {
    if (i < 16) return i;
    return 16 + 2 * (i & 7) + ((ib < 4) ^ ((i >> 3) & 1));
}

__device__ __forceinline__ void pin_value(uint32_t& v) { asm volatile("" : "+r"(v)); }
__device__ __forceinline__ void pin_value(int& v) { asm volatile("" : "+r"(v)); }
__device__ __forceinline__ void pin_value(const uint8_t*& v) { asm volatile("" : "+l"(v)); }

__device__ __forceinline__ void producer(const Params& P, uint32_t sb, int pair, int c,
                                         const CUtensorMap* m_ckv, const CUtensorMap* m_wuk, const CUtensorMap* m_wuv,
                                         const CUtensorMap* m_wq, const CUtensorMap* m_wo, const CUtensorMap* m_x,
                                         const CUtensorMap* m_out) {
    const int hl = pair >> 2;
    const int ibA = attn_rowblock(pair, 0), nA = 2 * ibA + 2;
    const int ib = (pair >> 1) & 7, mi = 2 * ib + c, nb = (pair >> 4) * 4 + (pair & 1) * 2;
    const bool leader = elect_one();
    uint32_t g = 4, tail = 0;
    if (leader) prefetch_map(m_wq);
    auto wait_released = [&](uint32_t need) {
#pragma unroll 1
        for (; tail <= need; tail++) mbar_wait(sb + BAR_EMPTY + (tail & 7) * 8, (tail >> 3) & 1);
    };
    auto wait_released_here = [&](uint32_t need) {
#pragma unroll 1
        for (; tail < need; tail++) mbar_wait(sb + BAR_EMPTY + (tail & 7) * 8, (tail >> 3) & 1);
        if (tail == need) mbar_wait(sb + BAR_EMPTYL + (need & 7) * 8, (need >> 3) & 1);
    };
    auto wait_released_peer = [&](uint32_t need) {
        if (tail == need) {
            uint32_t eb = sb + BAR_EMPTY + (need & 7) * 8, ep = (need >> 3) & 1;
            tail++;
            mbar_wait(eb, ep);
        }
    };
    auto full_bar = [&]() { return sb + BAR_FULL + (g & 7) * 8; };
    auto pin = [](auto&... v) { (pin_value(v), ...); };
#pragma unroll 1
    for (int rnd = 0; rnd < 2; rnd++) {
#pragma unroll 1
        for (int i = rnd ? 0 : 4; i < 16; i++) {
            const bool fresh = (i >> 2) != 2;
            int kb = (i ^ (i >> 1 & 4)) & 7, h2 = ((pair & 15) + rnd * 16) * 2 + c, krow = kb * 64, tok = (pair >> 4) * 512 + (i & 8) * 32 + c * 128;
            uint32_t pg = sb + (i & 3) * (3 * PAGE), pb = pg + (1 + c) * PAGE, bar = full_bar();
            pin(kb, h2, krow, tok, pg, pb, bar);
            const uint32_t need = g - 4 - (i < 2);
            wait_released_here(need);
            if (leader) {
                mbar_expect_tx(bar, fresh ? 3 * PAGE : 2 * PAGE);
                if (fresh) {
                    tma_3d(pg, m_wuk, 0, krow, h2, bar);
                    tma_3d(pg + 8192, m_wuv, 0, krow, h2, bar);
                }
            }
            wait_released_peer(need);
            if (leader) {
                tma_3d_mc(pb, m_ckv, 0, tok, kb, bar);
                if (rnd == 1 && i == 3) asm volatile("red.relaxed.gpu.global.add.u32 [%0], 1;" ::"l"(ptr_off(g_sync.kvfree, hl * 32)) : "memory");
            }
            g++;
        }
        mbar_sleep(sb + BAR_DEP, 0);
        const uint8_t* xa = ptr_off(g_xn, ibA * (16 * 32768) + c * PAGE);
        const uint8_t* xb = ptr_off(g_xn, (7 - ibA) * (16 * 32768) + (1 - c) * PAGE);
#pragma unroll 1
        for (int kb = 0; kb < DM / 64; kb++) {
            uint32_t pg = sb + (kb & 3) * (3 * PAGE), pw = pg + 2 * PAGE + c * 8192, bar = full_bar(), p2 = pg + PAGE;
            int krow = kb * 64;
            pin(pg, pw, p2, bar, krow);
            wait_released_here(g - 4);
            if (leader) {
                mbar_expect_tx(bar, 3 * PAGE);
                bulk_load(pg, xa, PAGE, bar);
            }
            wait_released_peer(g - 4);
            if (leader) {
                tma_3d_mc(pw, m_wq, 0, krow, (rnd * 16 + hl) * 2 + c, bar);
                bulk_load(p2, xb, PAGE, bar);
            }
            g++;
            xa += 32768;
            xb += 32768;
        }
        mbar_sleep(sb + BAR_DEP + 8 + rnd * 16, 0);
        if (rnd == 1 && leader) prefetch_map(m_wo);
        uint32_t pg = sb + c * PAGE;
#pragma unroll 1
        for (int j = 0; j < 36; j++) {
            const bool isk = j == 0 || ((j & 1) && j != 35);
            const int t = isk ? (j + 1) >> 1 : (j - 1) >> 1;
            const int n = t >= nA ? 18 - nA : nA, u = t >= nA ? t - nA : t, p1 = diag_place(n, 0), p2 = diag_place(n, 1);
            const int blk = u == p1 ? n - 2 : u == p2 ? n - 1 : u - (u > p1) - (u > p2);
            const uint8_t* src = ptr_off(g_kv, (hl * 16 + blk) * 65536 + (isk ? 0 : 32768) + c * PAGE);
            uint32_t bar = full_bar(), need = g - 6 + (j < 2) + (j < 5);
            pin(src, bar, need);
            wait_released(need);
            if (leader) {
                mbar_expect_tx(bar, 2 * PAGE);
                bulk_load_mc(pg, src, PAGE, bar);
            }
            g++;
            if (rnd == 0 && j >= 22 && j < 30) {
                const int cta = pair * 2 + c, i = j - 22;
                const uint32_t l = (threadIdx.x & 31) * 128;
                lsu_prefetch(ptr_off(i & 1 ? P.w_uv : P.w_uk, cta * 32768 + (i >> 1) * 8192 + 4096 + l));
            }
            if (rnd == 1 && j >= 32) {
                const int cta = pair * 2 + c, i = j - 32;
                const uint32_t l = (threadIdx.x & 31) * 128;
                lsu_prefetch(ptr_off(P.w_o, (i * 128 + cta) * 4096 + l));
            }
            pg = pg >= sb + SM_REGION - 2 * PAGE ? pg - (SM_REGION - 2 * PAGE) : pg + 2 * PAGE;
        }
    }
    uint32_t pg = sb;
#pragma unroll 1
    for (int i = 0; i < 64; i++) {
        if (i == 32 && leader) { prefetch_map(m_x); prefetch_map(m_out); }
        if ((i & 15) == 0 && i != 16) mbar_sleep(sb + BAR_DEP + 32 + (i >> 1) - (i ? 8 : 0), 0);
        const int kb = outproj_head(i >> 1, ib) * 2 + (i & 1);
        const uint8_t* src = ptr_off(g_ctx, (mi * 64 + kb) * PAGE);
        uint32_t bar = full_bar(), pw = pg + PAGE + c * 8192;
        int krow = kb * 2;
        pin(src, bar, pw, krow);
        wait_released_here(g - 6);
        if (leader) {
            mbar_expect_tx(bar, 2 * PAGE);
            bulk_load(pg, src, PAGE, bar);
        }
        wait_released_peer(g - 6);
        if (leader) tma_5d_mc(pw, m_wo, (nb + c) * 64, krow, bar);
        g++;
        pg = pg == sb + SM_REGION - 2 * PAGE ? sb : pg + 2 * PAGE;
    }
    const uint32_t bar = full_bar();
    wait_released(g - 6);
    if (leader) {
        mbar_expect_tx(bar, 2 * PAGE);
        tma_3d(pg, m_x, 0, mi * 128, nb, bar);
        tma_3d(pg + PAGE, m_x, 0, mi * 128 + 64, nb, bar);
    }
}

__device__ __forceinline__ uint32_t xn_block(int row64, int kb) {
    return (((row64 >> 2) * 16 + kb) * 4 + ((row64 & 1) * 2 + (((row64 >> 1) & 1) ^ 1))) * 8192;
}
__device__ __forceinline__ uint32_t image_offset(int row, int ch) {
    return xn_block(row >> 6, ch >> 3) + (row & 63) * 128 + (((ch & 7) ^ (row & 7)) << 4);
}
__device__ __forceinline__ uint32_t bf2_sub(uint32_t a, uint32_t b) {
    uint32_t r;
    asm("sub.rn.bf16x2 %0, %1, %2;" : "=r"(r) : "r"(a), "r"(b));
    return r;
}
__device__ __forceinline__ uint32_t bf2_fma(uint32_t a, uint32_t b, uint32_t c) {
    uint32_t r;
    asm("fma.rn.bf16x2 %0, %1, %2, %3;" : "=r"(r) : "r"(a), "r"(b), "r"(c));
    return r;
}
template <int N0, int N>
__device__ __forceinline__ void ln_sums(const uint32_t (&u)[N], float& sum, float& sq) {
    float s0 = 0.f, s1 = 0.f, q0 = 0.f, q1 = 0.f;
#pragma unroll
    for (int k = N0; k < N0 + 16; k++) {
        const float a = bf_lo(u[k]), b = bf_hi(u[k]);
        s0 += a; s1 += b;
        q0 = fmaf(a, a, q0); q1 = fmaf(b, b, q1);
    }
    sum = s0 + s1;
    sq = q0 + q1;
}
__device__ __forceinline__ void ln_finish(float sum, float sq, uint32_t& mean2, uint32_t& rhi2, uint32_t& rlo2) {
    const float ms = sum * (1.0f / DM);
    const float var = fmaxf(fmaf(-ms, ms, sq * (1.0f / DM)), 0.f);
    const float rden = rcp_approx(bf_round(sqrt_approx(bf_round(bf_round(var) + 1e-5f))));
    const float rhi = bf_round(rden);
    mean2 = pack_bf16(ms, ms);
    rhi2 = pack_bf16(rhi, rhi);
    rlo2 = pack_bf16(rden - rhi, rden - rhi);
}
template <int N0, int N>
__device__ __forceinline__ void ln_apply(const uint32_t (&u)[N], uint32_t mean2, uint32_t rhi2, uint32_t rlo2, uint8_t* dst) {
#pragma unroll
    for (int i = 0; i < 4; i++) {
        uint32_t o[4];
#pragma unroll
        for (int k = 0; k < 4; k++) {
            const uint32_t d = bf2_sub(u[N0 + 4 * i + k], mean2);
            o[k] = bf2_fma(d, rhi2, bf2_mul(d, rlo2));
        }
        __stcg(reinterpret_cast<uint4*>(dst + i * 131072), make_uint4(o[0], o[1], o[2], o[3]));
    }
}
__device__ __forceinline__ int query_rowblock(int pair, int c, int w, int seg) {
    const int qA = (w ? 0 : 2) + c;
    return 4 * attn_rowblock(pair, seg) + (seg ? 3 - qA : qA);
}

__device__ __forceinline__ void fetch_helper(const uint8_t* c_kv, uint32_t sb, int w, int lane, int pair, int c) {
    const uint32_t page = sb + SM_REGION + w * PAGE + lane * 16;
    mbar_sleep(sb + BAR_FULL + 5 * 8, 0);
    lsu_prefetch(ptr_off(c_kv, (pair >> 4) * 524288 + 262144 + ((pair & 15) * 4 + c * 2 + w) * 4096 + lane * 128));
    const unsigned e1 = __ldcg(&g_sync.done) / NCTA + 1;
#pragma unroll 1
    for (int e = 1; e <= 7; e += 2) mbar_sleep(sb + BAR_DONE + 8, (e >> 1) & 1);
    const int rb = ((pair >> 1) & 7) * 4 + c * 2 + w, kb0 = (pair >> 4) * 4 + (pair & 1) * 2;
    const uint8_t* src = ptr_off(g_xn, xn_block(rb, kb0) + lane * 16);
#pragma unroll 1
    for (int i = 0; i < 32; i += 4) {
#pragma unroll
        for (int k = 0; k < 4; k++) cp_async16(page + (i + k) * 512, src + (i + k) * 512 + (i >> 4) * (32768 - 8192));
        __nanosleep(200);
    }
    wait_counter(&g_sync.ffn_done, e1);
    const int r = __ldcg(ptr_off(g_sel, (lane >> 4) * 4)) - rb * 64, ch = lane & 15;
    const uint4 t = __ldcg(ptr_off(g_routed, ((lane >> 4) * 128 + kb0 * 8 + ch) * 16));
    asm volatile("cp.async.wait_all;" ::: "memory");
    __syncwarp();
    if (r >= 0 && r < 64)
        sts128(sb + SM_REGION + w * PAGE + (ch >> 3) * 8192 + r * 128 + (((ch & 7) ^ (r & 7)) << 4), t.x, t.y, t.z, t.w);
    __syncwarp();
    if (lane == 0) mbar_arrive(sb + BAR_G + w * 8);
    PROF(20, 2);
}

__device__ __noinline__ void sync_helper(uint32_t sb, int lane, int pair, int c) {
    const unsigned e1 = __ldcg(&g_sync.done) / NCTA + 1;
    const int ib = (pair >> 1) & 7;
    int e = 0, b = 0;
#pragma unroll 1
    for (uint32_t n = 0; (e < 9 || b < 7) && n < SPIN_LIMIT; n++) {
        if (e < 9 && __all_sync(~0u, mbar_test(sb + BAR_DONE + (e & 1) * 8, (e >> 1) & 1))) {
            const int rnd = e > 4, ev = (e - 1) & 3;
            unsigned* flag = e == 0 ? &g_sync.ln
                           : ev < 2 ? ptr_off(g_sync.kv, (rnd * 16 + (pair & 15)) * 32)
                                    : ptr_off(g_sync.ctx, (query_rowblock(pair, c, lane & 1, ev & 1) * NH + rnd * 16 + (pair >> 2)) * 4);
            asm volatile("fence.proxy.async.global;\nfence.release.gpu;" ::: "memory");
            if (lane < ((e == 0 || ev < 2) ? 1 : 2)) asm volatile("red.relaxed.gpu.global.add.u32 [%0], 1;" ::"l"(flag) : "memory");
            PROF(10 + e, 2);
            e++;
        }
        if (b < 7 && e > 0 && (b < 4 || (n & POLL_MASK) == 0)) {
            const int i = b == 4 ? lane >> 1 : 8 * b - 24 + ((lane >> 1) & 7);
            const unsigned* cnt = b == 0 ? &g_sync.ln
                                : b == 2 ? ptr_off(g_sync.kvfree, (pair & 15) * 32)
                                : b < 4 ? ptr_off(g_sync.kv, ((b >> 1) * 16 + (pair >> 2)) * 32)
                                        : ptr_off(g_sync.ctx, ((4 * ib + 2 * c + (lane & 1)) * NH + outproj_head(i & 31, ib)) * 4);
            if (__all_sync(~0u, (int)(ld_relaxed(cnt) - e1 * (b == 0 ? NMAIN : b == 2 ? 8 : b < 4 ? 16 : 1)) >= 0)) {
                asm volatile("fence.acquire.gpu;\nfence.proxy.async.global;" ::: "memory");
                __syncwarp();
                if (lane == 0) mbar_arrive(sb + BAR_DEP + b * 8);
                PROF(1 + b, 2);
                b++;
            }
        }
        __nanosleep(150);
    }
}

__device__ __forceinline__ unsigned long long block_max_key(unsigned long long k, unsigned long long* red, int tid) {
#pragma unroll
    for (int o = 16; o; o >>= 1) {
        unsigned long long t = __shfl_xor_sync(~0u, k, o);
        k = t > k ? t : k;
    }
    bar_sync(1, 256);
    if ((tid & 31) == 0) red[tid >> 5] = k;
    bar_sync(1, 256);
    k = red[0];
#pragma unroll
    for (int i = 1; i < 8; i++) k = red[i] > k ? red[i] : k;
    return k;
}

constexpr int FS = FF / 4;
constexpr int FSTAGE = 32768, FNST = 6;
constexpr int FN0 = 32, FN1 = 2 * (DM / 16), FN2 = FS / 16;
constexpr uint32_t XB = FNST * FSTAGE, HB = XB + 16384, AUX = HB + 14336, PAUSE = AUX + 192;
constexpr int PAUSE_AT = 100;

__device__ __forceinline__ void ffn_producer(uint32_t sb, int s, unsigned e1, const CUtensorMap* m_gate, const CUtensorMap* m_up,
                                             const CUtensorMap* m_down) {
    const uint64_t pol = policy_evict_first();
    int slot = 0, ph = 1;
    wait_counter(&g_sync.ln, e1 * NMAIN);
#pragma unroll 1
    for (int st = -FN0; st < FN1 + FN2; st++) {
        mbar_sleep(sb + BAR_EMPTY + slot * 8, ph);
        const uint32_t bar = sb + BAR_FULL + slot * 8;
        if (st < 0) {
            mbar_expect_tx(bar, FSTAGE);
            bulk_load(sb + slot * FSTAGE, ptr_off(g_xn, (s * FN0 + FN0 + st) * FSTAGE), FSTAGE, bar);
        } else {
            if (st >= PAUSE_AT) {
                uint32_t p;
                for (uint32_t n = 0; n < 100; n++) {
                    asm volatile("ld.volatile.shared.u32 %0, [%1];" : "=r"(p) : "r"(sb + PAUSE) : "memory");
                    if (!p) break;
                    __nanosleep(200);
                }
            }
            const bool up = st < FN1;
            mbar_expect_tx(bar, up ? FS * 32 : DM * 32);
            tma_3d_hint(sb + slot * FSTAGE, up ? ((st & 1) ? m_up : m_gate) : m_down, 0,
                        up ? (st >> 1) * 16 : s * FS + (st - FN1) * 16, up ? s * (FS / 64) : 0, bar, pol);
        }
        if (++slot == FNST) { slot = 0; ph ^= 1; }
    }
}
__device__ __forceinline__ void ffn_pacer(uint32_t sb, unsigned e1) {
    wait_counter(&g_sync.kvfree[0], e1 * 8, 500);
    asm volatile("st.volatile.shared.u32 [%0], 1;" ::"r"(sb + PAUSE) : "memory");
    wait_counter(&g_sync.kv[16 * 8], e1 * 16, 500);
    asm volatile("st.volatile.shared.u32 [%0], 0;" ::"r"(sb + PAUSE) : "memory");
}

__device__ __forceinline__ void ffn_cta(uint8_t* smem, uint32_t sb, int s, unsigned epoch, const __nv_bfloat16* w_r) {
    const int tid = threadIdx.x, lane = tid & 31;
    const int warp = __shfl_sync(~0u, tid >> 5, 0), w = warp >> 2;
    unsigned long long* red = reinterpret_cast<unsigned long long*>(smem + AUX);
    unsigned* flag = reinterpret_cast<unsigned*>(smem + AUX + 128);
    const unsigned e1 = epoch + 1;
    for (int i = tid; i < (16384 + 14336) / 16; i += 256) reinterpret_cast<uint4*>(smem + XB)[i] = make_uint4(0, 0, 0, 0);
    int slot = 0, ph = 0, prev = 0;
    auto next_stage = [&](bool has_prev) {
        wg_commit();
        wg_wait<1>();
        if (has_prev && lane < 2) mbar_arrive(sb + BAR_EMPTY + prev * 8);
        prev = slot;
        if (++slot == FNST) { slot = 0; ph ^= 1; }
    };
    {
        bar_sync(1, 256);
        if (tid < 128) *reinterpret_cast<uint4*>(smem + XB + (tid >> 3) * 1024 + (tid & 7) * 16) = __ldg(reinterpret_cast<const uint4*>(w_r) + tid);
        fence_async_smem();
        bar_sync(1, 256);
#pragma unroll 1
        for (int blk = 0; blk < 2; blk++) {
            float ar[8];
#pragma unroll
            for (int i = 0; i < 8; i++) ar[i] = 0.f;
#pragma unroll 1
            for (int kb = 0; kb < 16; kb++) {
                const uint64_t db = make_desc(sb + XB + kb * 1024, 16);
                mbar_wait(sb + BAR_FULL + slot * 8, ph);
                const uint64_t da = make_desc(sb + slot * FSTAGE + w * 16384, 16);
                wg_fence();
#pragma unroll
                for (int q = 0; q < 4; q++) {
                    wgmma_n8(ar, da + 2 * q, db + 2 * q);
                    wgmma_n8(ar + 4, da + 512 + 2 * q, db + 2 * q);
                }
                next_stage(blk + kb > 0);
            }
            wg_wait<0>();
            reg_fence(ar);
            if ((lane & 3) == 0) {
#pragma unroll
                for (int i = 0; i < 4; i++)
                    __stcg(&g_r[(s * 2 + blk) * 256 + (w + 2 - (i & 2)) * 64 + (warp & 3) * 16 + (lane >> 2) + (i & 1) * 8], bf_round(ar[2 * i]));
            }
        }
        __threadfence();
        bar_sync(1, 256);
        if (tid == 0) {
            red_release(&g_sync.router);
            wait_counter(&g_sync.router, e1 * 4);
        }
        bar_sync(1, 256);
    }
    unsigned long long keys[8];
    unsigned long long best = 0;
#pragma unroll
    for (int i = 0; i < 8; i++) {
        int idx = tid + 256 * i;
        uint32_t b = __float_as_uint(__ldcg(&g_r[idx]) + 0.0f);
        b = (b & 0x80000000u) ? ~b : (b | 0x80000000u);
        keys[i] = ((unsigned long long)b << 32) | (unsigned)(SEQ - 1 - idx);
        best = keys[i] > best ? keys[i] : best;
    }
    const unsigned long long k0 = block_max_key(best, red, tid);
    best = 0;
#pragma unroll
    for (int i = 0; i < 8; i++) best = (keys[i] != k0 && keys[i] > best) ? keys[i] : best;
    const unsigned long long k1 = block_max_key(best, red, tid);
    const int row = SEQ - 1 - (int)((w ? k1 : k0) & 0xffffffffu);
    const int ch = tid & 127;
    const uint4 xrow = __ldcg(reinterpret_cast<const uint4*>(g_xn + image_offset(row, ch)));
    *reinterpret_cast<uint4*>(smem + XB + (ch >> 3) * 1024 + w * 128 + (((ch & 7) ^ w) << 4)) = xrow;
    fence_async_smem();
    bar_sync(1, 256);
    PROF(20, tid >> 7);
    {
        float ag[28], au[28];
#pragma unroll
        for (int i = 0; i < 28; i++) ag[i] = au[i] = 0.f;
#pragma unroll 1
        for (int ks = 0; ks < DM / 16; ks++) {
            const uint64_t db = make_desc(sb + XB + (ks >> 2) * 1024 + (ks & 3) * 32, 16);
            mbar_wait(sb + BAR_FULL + slot * 8, ph);
            uint64_t da = make_desc(sb + slot * FSTAGE + w * (7 * 2048), 16);
            wg_fence();
#pragma unroll
            for (int b = 0; b < 7; b++) wgmma_n8_ta(ag + 4 * b, da + b * 128, db);
            next_stage(true);
            mbar_wait(sb + BAR_FULL + slot * 8, ph);
            da = make_desc(sb + slot * FSTAGE + w * (7 * 2048), 16);
            wg_fence();
#pragma unroll
            for (int b = 0; b < 7; b++) wgmma_n8_ta(au + 4 * b, da + b * 128, db);
            next_stage(true);
        }
        wg_wait<0>();
        reg_fence(ag);
        reg_fence(au);
        if ((lane & 3) == 0) {
#pragma unroll
            for (int i = 0; i < 28; i++) {
                const int f = (warp & 3) * 16 + (lane >> 2) + (i & 2) * 4, tok = i & 1;
                const float h = bf_round(silu_f(bf_round(ag[i]))) * bf_round(au[i]);
                *reinterpret_cast<__nv_bfloat16*>(smem + HB + (w * 7 + (i >> 2)) * 1024 + tok * 128 + (((f >> 3) ^ tok) << 4) + (f & 7) * 2) =
                    __float2bfloat16_rn(h);
            }
        }
    }
    fence_async_smem();
    bar_sync(1, 256);
    PROF(21, tid >> 7);
    {
        float ay[32];
#pragma unroll
        for (int i = 0; i < 32; i++) ay[i] = 0.f;
#pragma unroll 1
        for (int ks = 0; ks < FN2; ks++) {
            const uint64_t db = make_desc(sb + HB + (ks >> 2) * 1024 + (ks & 3) * 32, 16);
            mbar_wait(sb + BAR_FULL + slot * 8, ph);
            const uint64_t da = make_desc(sb + slot * FSTAGE + w * (8 * 2048), 16);
            wg_fence();
#pragma unroll
            for (int b = 0; b < 8; b++) wgmma_n8_ta(ay + 4 * b, da + b * 128, db);
            next_stage(true);
        }
        wg_wait<0>();
        reg_fence(ay);
        if ((lane & 3) == 0) {
#pragma unroll
            for (int i = 0; i < 32; i++)
                g_ypart[(s * 2 + (i & 1)) * DM + (w * 8 + (i >> 2)) * 64 + (warp & 3) * 16 + (lane >> 2) + (i & 2) * 4] = ay[i];
        }
    }
    PROF(23, tid >> 7);
    __threadfence();
    bar_sync(1, 256);
    if (tid == 0) {
        *flag = atomicAdd(&g_sync.ffn_ticket, 1u) == epoch * 4 + 3;
        __threadfence();
    }
    bar_sync(1, 256);
    if (*flag) {
        const float sg = bf_round(__fdividef(1.0f, 1.0f + __expf(-__ldcg(&g_r[row]))));
        const uint32_t xu[4] = {xrow.x, xrow.y, xrow.z, xrow.w};
        uint32_t o[4];
#pragma unroll
        for (int k = 0; k < 4; k++) {
            float y0 = 0.f, y1 = 0.f;
#pragma unroll
            for (int q = 0; q < 4; q++) {
                const float2 y = __ldcg(reinterpret_cast<const float2*>(&g_ypart[(q * 2 + w) * DM + ch * 8 + 2 * k]));
                y0 += y.x; y1 += y.y;
            }
            o[k] = pack_bf16(bf_lo(xu[k]) + bf_round(bf_round(y0) * sg), bf_hi(xu[k]) + bf_round(bf_round(y1) * sg));
        }
        g_routed[w * 128 + ch] = make_uint4(o[0], o[1], o[2], o[3]);
        if (ch == 0) g_sel[w] = row;
        bar_sync(1, 256);
        if (tid == 0) red_release(&g_sync.ffn_done);
    }
}

__device__ __forceinline__ uint32_t slab_addr(uint32_t stg, int lane, int s) {
    const int row = ((lane >> 3) & 1) * 8 + (lane & 7);
    const int chunk = 2 * (s & 3) + (lane >> 4);
    return stg + row * 128 + (s >> 2) * 8192 + ((chunk ^ (lane & 7)) << 4);
}

constexpr float SM_SCALE = 0.08838834764831845f * 1.4426950408889634f;
constexpr float SUM_HI = 1048576.f, SUM_LO = 1.0f / 1048576.f;

template <int J0>
__device__ __forceinline__ void mask_half(float (&S)[64], float limf) {
    asm volatile("" : "+f"(limf));
#pragma unroll
    for (int i = 0; i < 32; i++) {
        const int j = i >> 2, key = 32 * (j >> 2) + 2 * (j & 3) + (i & 1) - 4 * (i & 2);
        float t;
        asm("add.sat.f32 %0, %1, %2;" : "=f"(t) : "f"((float)key), "f"(-limf));
        S[4 * J0 + i] = fmaf(t, -1e30f, S[4 * J0 + i]);
    }
}
__device__ __forceinline__ void issue_qk(float (&S)[64], const uint32_t (&Q)[32], uint64_t d0) {
#pragma unroll
    for (int s = 0; s < 8; s++)
        wgmma_n128_rs<1>(S, Q[4 * s], Q[4 * s + 1], Q[4 * s + 2], Q[4 * s + 3], d0 + s * 128, s > 0);
}
template <int S0, int S1>
__device__ __forceinline__ void issue_pv(float (&O)[64], const uint32_t (&Pm)[32], uint64_t d0, int acc) {
#pragma unroll
    for (int s = S0; s < S1; s++)
        wgmma_n128_rs<0>(O, Pm[4 * s], Pm[4 * s + 1], Pm[4 * s + 2], Pm[4 * s + 3], d0 + (s >> 2) * (PAGE >> 4) + (s & 3) * 2, s > 0 ? 1 : acc);
}
template <int J0, int J1>
__device__ __forceinline__ void exp_part(const float (&S)[64], uint32_t (&Pm)[32], float (&sum)[4]) {
#pragma unroll
    for (int i = 2 * J0; i < 2 * J1; i++) asm volatile("" : "+r"(Pm[i])::"memory");
#pragma unroll
    for (int j = J0; j < J1; j++) {
        const float e0 = ex2(S[4 * j]), e1 = ex2(S[4 * j + 1]), e2 = ex2(S[4 * j + 2]), e3 = ex2(S[4 * j + 3]);
        sum[0] += e0; sum[1] += e1; sum[2] += e2; sum[3] += e3;
        Pm[2 * j] = pack_bf16(e0, e1);
        Pm[2 * j + 1] = pack_bf16(e2, e3);
    }
}
__device__ __forceinline__ void shift_rows(float (&S)[64], float d0, float d1) {
#pragma unroll
    for (int j = 0; j < 16; j++) {
        S[4 * j] -= d0; S[4 * j + 1] -= d0; S[4 * j + 2] -= d1; S[4 * j + 3] -= d1;
    }
}
__device__ __forceinline__ void sched_fence(uint32_t& tick, bool on) {
    asm volatile("{\n.reg .pred p;\nsetp.ne.u32 p, %1, 0;\n@p mov.u32 %0, %%clock;\n}\n" : "+r"(tick) : "r"((uint32_t)on) : "memory");
}
constexpr int LAG = 4;
struct NoExtra { __device__ __forceinline__ void operator()(int) const {} };
template <int K0, int K1, int NP, int WAITAT, typename X = NoExtra>
__device__ __forceinline__ void exp_stages(const float (&S)[64], float (&e)[64], uint32_t (&Pm)[32], float (&sum)[4], uint32_t& tick, bool on,
                                           X extra = X()) {
#pragma unroll
    for (int k = K0; k < K1; k++) {
        if (k == WAITAT) wg_wait<1>();
        if (k < NP) {
            asm volatile("ex2.approx.ftz.f32 %0, %1;" : "=f"(e[2 * k]) : "f"(S[2 * k]));
            asm volatile("ex2.approx.ftz.f32 %0, %1;" : "=f"(e[2 * k + 1]) : "f"(S[2 * k + 1]));
        }
        if (k >= LAG) {
            const int i = 2 * (k - LAG);
            asm volatile("add.f32 %0, %0, %1;" : "+f"(sum[i & 3]) : "f"(e[i]));
            asm volatile("add.f32 %0, %0, %1;" : "+f"(sum[(i & 3) + 1]) : "f"(e[i + 1]));
            asm volatile("cvt.rn.bf16x2.f32 %0, %1, %2;" : "=r"(Pm[i / 2]) : "f"(e[i + 1]), "f"(e[i]));
        }
        extra(k);
        if (k >= LAG - 1 && k < NP - 1 && k != K1 - 1) sched_fence(tick, on);
    }
}
__device__ constexpr int chunk_src(int i) { return 4 * (4 * (i >> 3) + (i & 3)) + 2 * ((i >> 2) & 1); }
enum : uint32_t { CTL_START = 1, CTL_SWITCH = 2, CTL_DIRECT = 4, CTL_HALF = 8, CTL_MASKHI = 16, CTL_LOADQ = 32, CTL_PVHALF = 64, CTL_PVACC = 128,
                  CTL_SKIPREL = 256 };
__device__ __forceinline__ float quad_sum(float v) {
    v += __shfl_xor_sync(~0u, v, 1);
    return v + __shfl_xor_sync(~0u, v, 2);
}

__device__ __forceinline__ void store_part(uint8_t* d0, int p, const uint32_t (&pk)[64]) {
    asm volatile("{\n.reg .b64 d1;\nxor.b64 d1, %0, 64;\n"
                 "TS: .branchtargets P0, P1, P2, P3, P4, P5, P6, P7;\n"
                 "brx.idx.uni %1, TS;\n"
                 "P0:\n st.global.cs.v4.u32 [%0 + 0], {%2, %3, %4, %5};\n st.global.cs.v4.u32 [d1 + 0], {%10, %11, %12, %13};\n bra.uni DONE;\n"
                 "P1:\n st.global.cs.v4.u32 [%0 + 1024], {%6, %7, %8, %9};\n st.global.cs.v4.u32 [d1 + 1024], {%14, %15, %16, %17};\n bra.uni DONE;\n"
                 "P2:\n st.global.cs.v4.u32 [%0 + 16384], {%18, %19, %20, %21};\n st.global.cs.v4.u32 [d1 + 16384], {%26, %27, %28, %29};\n bra.uni DONE;\n"
                 "P3:\n st.global.cs.v4.u32 [%0 + 17408], {%22, %23, %24, %25};\n st.global.cs.v4.u32 [d1 + 17408], {%30, %31, %32, %33};\n bra.uni DONE;\n"
                 "P4:\n st.global.cs.v4.u32 [%0 + 65536], {%34, %35, %36, %37};\n st.global.cs.v4.u32 [d1 + 65536], {%42, %43, %44, %45};\n bra.uni DONE;\n"
                 "P5:\n st.global.cs.v4.u32 [%0 + 66560], {%38, %39, %40, %41};\n st.global.cs.v4.u32 [d1 + 66560], {%46, %47, %48, %49};\n bra.uni DONE;\n"
                 "P6:\n st.global.cs.v4.u32 [%0 + 81920], {%50, %51, %52, %53};\n st.global.cs.v4.u32 [d1 + 81920], {%58, %59, %60, %61};\n bra.uni DONE;\n"
                 "P7:\n st.global.cs.v4.u32 [%0 + 82944], {%54, %55, %56, %57};\n st.global.cs.v4.u32 [d1 + 82944], {%62, %63, %64, %65};\n bra.uni DONE;\n"
                 "DONE:\n}\n"
                 ::"l"(d0), "r"(p), "r"(pk[0]), "r"(pk[1]), "r"(pk[2]), "r"(pk[3]), "r"(pk[4]), "r"(pk[5]), "r"(pk[6]), "r"(pk[7]), "r"(pk[8]), "r"(pk[9]), "r"(pk[10]), "r"(pk[11]), "r"(pk[12]), "r"(pk[13]), "r"(pk[14]), "r"(pk[15]), "r"(pk[16]), "r"(pk[17]), "r"(pk[18]), "r"(pk[19]), "r"(pk[20]), "r"(pk[21]), "r"(pk[22]), "r"(pk[23]), "r"(pk[24]), "r"(pk[25]), "r"(pk[26]), "r"(pk[27]), "r"(pk[28]), "r"(pk[29]), "r"(pk[30]), "r"(pk[31]), "r"(pk[32]), "r"(pk[33]), "r"(pk[34]), "r"(pk[35]), "r"(pk[36]), "r"(pk[37]), "r"(pk[38]), "r"(pk[39]), "r"(pk[40]), "r"(pk[41]), "r"(pk[42]), "r"(pk[43]), "r"(pk[44]), "r"(pk[45]), "r"(pk[46]), "r"(pk[47]), "r"(pk[48]), "r"(pk[49]), "r"(pk[50]), "r"(pk[51]), "r"(pk[52]), "r"(pk[53]), "r"(pk[54]), "r"(pk[55]), "r"(pk[56]), "r"(pk[57]), "r"(pk[58]), "r"(pk[59]), "r"(pk[60]), "r"(pk[61]), "r"(pk[62]), "r"(pk[63])
                 : "memory");
}

__device__ __forceinline__ void store_part4(uint8_t* d0, int p, const uint32_t (&pk)[64]) {
    asm volatile("{\n.reg .b64 d1;\nxor.b64 d1, %0, 64;\n"
                 "TS: .branchtargets P0, P1, P2, P3;\n"
                 "brx.idx.uni %1, TS;\n"
                 "P0:\n st.global.cs.v4.u32 [%0 + 0], {%2, %3, %4, %5};\n st.global.cs.v4.u32 [d1 + 0], {%10, %11, %12, %13};\n bra.uni DONE;\n"
                 "P1:\n st.global.cs.v4.u32 [%0 + 1024], {%6, %7, %8, %9};\n st.global.cs.v4.u32 [d1 + 1024], {%14, %15, %16, %17};\n bra.uni DONE;\n"
                 "P2:\n st.global.cs.v4.u32 [%0 + 16384], {%18, %19, %20, %21};\n st.global.cs.v4.u32 [d1 + 16384], {%26, %27, %28, %29};\n bra.uni DONE;\n"
                 "P3:\n st.global.cs.v4.u32 [%0 + 17408], {%22, %23, %24, %25};\n st.global.cs.v4.u32 [d1 + 17408], {%30, %31, %32, %33};\n bra.uni DONE;\n"
                 "DONE:\n}\n"
                 ::"l"(d0), "r"(p), "r"(pk[0]), "r"(pk[1]), "r"(pk[2]), "r"(pk[3]), "r"(pk[4]), "r"(pk[5]), "r"(pk[6]), "r"(pk[7]), "r"(pk[8]), "r"(pk[9]), "r"(pk[10]), "r"(pk[11]), "r"(pk[12]), "r"(pk[13]), "r"(pk[14]), "r"(pk[15]), "r"(pk[16]), "r"(pk[17]), "r"(pk[18]), "r"(pk[19]), "r"(pk[20]), "r"(pk[21]), "r"(pk[22]), "r"(pk[23]), "r"(pk[24]), "r"(pk[25]), "r"(pk[26]), "r"(pk[27]), "r"(pk[28]), "r"(pk[29]), "r"(pk[30]), "r"(pk[31])
                 : "memory");
}

__device__ __forceinline__ void set_quad(uint32_t (&d)[32], int p, uint32_t u0, uint32_t u1, uint32_t u2, uint32_t u3) {
    asm volatile("{\nTG: .branchtargets G0, G1, G2, G3, G4, G5, G6, G7;\n"
                 "brx.idx.uni %32, TG;\n"
                 "G0:\n mov.b32 %0, %33;\n mov.b32 %1, %34;\n mov.b32 %2, %35;\n mov.b32 %3, %36;\n bra.uni DONE;\n"
                 "G1:\n mov.b32 %4, %33;\n mov.b32 %5, %34;\n mov.b32 %6, %35;\n mov.b32 %7, %36;\n bra.uni DONE;\n"
                 "G2:\n mov.b32 %8, %33;\n mov.b32 %9, %34;\n mov.b32 %10, %35;\n mov.b32 %11, %36;\n bra.uni DONE;\n"
                 "G3:\n mov.b32 %12, %33;\n mov.b32 %13, %34;\n mov.b32 %14, %35;\n mov.b32 %15, %36;\n bra.uni DONE;\n"
                 "G4:\n mov.b32 %16, %33;\n mov.b32 %17, %34;\n mov.b32 %18, %35;\n mov.b32 %19, %36;\n bra.uni DONE;\n"
                 "G5:\n mov.b32 %20, %33;\n mov.b32 %21, %34;\n mov.b32 %22, %35;\n mov.b32 %23, %36;\n bra.uni DONE;\n"
                 "G6:\n mov.b32 %24, %33;\n mov.b32 %25, %34;\n mov.b32 %26, %35;\n mov.b32 %27, %36;\n bra.uni DONE;\n"
                 "G7:\n mov.b32 %28, %33;\n mov.b32 %29, %34;\n mov.b32 %30, %35;\n mov.b32 %31, %36;\n bra.uni DONE;\n"
                 "DONE:\n}\n"
                 : "+r"(d[0]), "+r"(d[1]), "+r"(d[2]), "+r"(d[3]), "+r"(d[4]), "+r"(d[5]), "+r"(d[6]), "+r"(d[7]), "+r"(d[8]), "+r"(d[9]), "+r"(d[10]), "+r"(d[11]), "+r"(d[12]), "+r"(d[13]), "+r"(d[14]), "+r"(d[15]), "+r"(d[16]), "+r"(d[17]), "+r"(d[18]), "+r"(d[19]), "+r"(d[20]), "+r"(d[21]), "+r"(d[22]), "+r"(d[23]), "+r"(d[24]), "+r"(d[25]), "+r"(d[26]), "+r"(d[27]), "+r"(d[28]), "+r"(d[29]), "+r"(d[30]), "+r"(d[31])
                 : "r"(p), "r"(u0), "r"(u1), "r"(u2), "r"(u3));
}

__device__ __forceinline__ void consumer(uint32_t sb, int pair, int c, const CUtensorMap* m_out, const uint8_t* x) {
    const int tid = threadIdx.x;
    const int warp = __shfl_sync(~0u, tid >> 5, 0);
    const int w = warp >> 2, v = warp & 3, lane = tid & 31;
    constexpr uint64_t desc_hi = ((uint64_t)(1024 >> 4) << 32) | (1ull << 62);

    const uint32_t empty_rel = lane == 2 ? mapa(sb + BAR_EMPTYL, c) : mapa(sb + BAR_EMPTY, lane & 1);
    auto release = [&](uint32_t grp) {
        if (lane < 3) mbar_arrive_cluster(empty_rel + (grp & 7) * 8);
    };
    auto wait_full = [&](uint32_t grp) { mbar_wait(sb + BAR_FULL + (grp & 7) * 8, (grp >> 3) & 1); };

    uint32_t g = 0;
    const uint32_t stg = sb + SM_REGION + w * PAGE + v * 2048;
    const uint32_t chunk0 = (lane >> 2) * 128 + (((lane & 3) ^ (lane >> 2)) << 4);
    uint32_t ndone = 0;
    auto mark_done = [&]() {
        __syncwarp();
        if (lane == 0) mbar_arrive(sb + BAR_DONE + ndone);
        ndone ^= 8;
    };
    auto ctx_dst = [&](int rnd, int seg) {
        const int rb = query_rowblock(pair, c, w, seg);
        return ptr_off(g_ctx, ((rb >> 1) * 64 + (rnd * 16 + (pair >> 2)) * 2) * PAGE + (rb & 1) * 8192 + v * 2048);
    };

    uint32_t ctl_tab;
    {
        const int t = lane, nA = 2 * attn_rowblock(pair, 0) + 2, nB = 18 - nA, firstB = nA - w;
        const int tA = w ? diag_place(nA, 0) : diag_place(nA, 1), tB = w ? nA + diag_place(nB, 1) - 1 : nA + diag_place(nB, 0);
        const int ts = w ? diag_place(nA, 1) - 1 : nA + diag_place(nB, 1) - 1;
        auto is_half = [&](int u) { return (u == tA && c == 0) || (u == tB && c == 1); };
        const bool diag = t == tA || t == tB;
        const int kadv = (t == 0 ? 1 : 2) + (t == ts ? 2 : 0);
        const int vadv = 2 + (t == ts + 1 ? 2 : 0) - (t == 16 ? 1 : 0);
        ctl_tab = (t == 0 ? CTL_START : 0) | (t == firstB ? CTL_SWITCH : 0) | (t == ts + 1 ? CTL_SKIPREL : 0) |
                  (diag ? (is_half(t) ? CTL_HALF : CTL_MASKHI) : 0) | (t == firstB - 1 ? (t ? CTL_LOADQ : CTL_DIRECT) : 0) |
                  ((t > 0 && is_half(t - 1)) ? CTL_PVHALF : 0) | ((t == 1 || t == firstB + 1) ? 0 : CTL_PVACC) |
                  (kadv << 16) | (vadv << 20);
    }

    uint32_t pk[64];
#pragma unroll
    for (int i = 0; i < 64; i++) pk[i] = 0;
    uint8_t* pend = nullptr;
    auto write_part = [&](int p) { store_part(pend, p, pk); };
    if (w == 1) bar_arrive(2, 256);
    asm volatile("barrier.cluster.wait.aligned;" ::: "memory");
    {
        const uint8_t* src = ptr_off(x, ((pair * 2 + c) * 16 + warp * 2) * (DM * 2) + lane * 16);
#pragma unroll
        for (int i = 0; i < 5; i++) {
            uint4 t;
            asm volatile("ld.global.cg.v4.u32 {%0, %1, %2, %3}, [%4];" : "=r"(t.x), "=r"(t.y), "=r"(t.z), "=r"(t.w) : "l"(src + i * 512) : "memory");
            pk[4 * i] = t.x; pk[4 * i + 1] = t.y; pk[4 * i + 2] = t.z; pk[4 * i + 3] = t.w;
        }
    }
    asm volatile("cp.async.wait_all;" ::: "memory");
    fence_async_smem();
    bar_sync(4, 256);

    float O[64], l[2] = {0.f, 0.f};
    auto finish_attention = [&](int rnd, uint32_t ge) {
        const float i0 = rcp_approx(quad_sum(l[0])), i1 = rcp_approx(quad_sum(l[1]));
        if (rnd) wg_wait<1>(); else wg_wait<0>();
        reg_fence(O);
        release(ge - 1);
#pragma unroll
        for (int i = 0; i < 32; i++) {
            const float sc = (i & 4) ? i1 : i0;
            pk[i] = pack_bf16(O[chunk_src(i)] * sc, O[chunk_src(i) + 1] * sc);
        }
        pend = ptr_off(ctx_dst(rnd, 1), chunk0);
#pragma unroll
        for (int i = 32; i < 64; i++) pk[i] = 0;
    };
    for (int item = 0;; item++) {
        if (item != 2 && item != 5) {
            constexpr int nk = DC / 64;
            float acc[128];
            auto issue_kblock = [&](int first_acc) {
                wait_full(g);
                const uint32_t pg = sb + (g & 3) * (3 * PAGE);
                const uint64_t da = make_desc(pg + w * 8192, 16), db = make_desc(pg + PAGE, 16);
                wg_fence();
#pragma unroll
                for (int q = 0; q < 4; q++) wgmma_n256_ss(acc, da + 128 * q, db + 2 * q, q ? 1 : first_acc);
                wg_commit();
                g++;
            };
            if (item == 0) PROF(17, w);
            issue_kblock(0);
            if (item == 0) PROF(1, w);
            if (item == 0 && w == 0) PROF_GT(1);
            const int nparts = item == 0 ? 0 : (item == 3 ? 4 : 8);
            const int ln_row = (pair * 2 + c) * 16 + warp * 2;
            if (item == 0) {
                const uint8_t* src = ptr_off(x, ln_row * (DM * 2) + lane * 16);
#pragma unroll
                for (int i = 5; i < 8; i++) {
                    const uint4 t = __ldcg(reinterpret_cast<const uint4*>(src + i * 512));
                    pk[4 * i] = t.x; pk[4 * i + 1] = t.y; pk[4 * i + 2] = t.z; pk[4 * i + 3] = t.w;
                }
            }
#pragma unroll 1
            for (int kb = 1; kb < nk; kb++) {
                if (kb == nk - 2 && w == 1) bar_sync(4, 256);
                issue_kblock(1);
                if (kb == nk - 1 && w == 0) bar_arrive(4, 256);
                if (kb <= nparts) {
                    if (item == 4 && kb == 1) mbar_wait(sb + BAR_DEP + 16, 0);
                    write_part(kb - 1);
                    if (kb == nk - 1) write_part(nk - 1);
                    if (kb == nparts || kb == nk - 1) mark_done();
                }
                wg_wait<1>();
                release(g - 2);
                if (g >= 4 && g <= 8) {
                    float s[2], q[2];
                    if (g == 4) {
                        ln_sums<0>(pk, s[0], q[0]);
                        pk[32] = __float_as_uint(s[0]); pk[33] = __float_as_uint(q[0]);
                    }
                    if (g == 5) {
                        ln_sums<16>(pk, s[1], q[1]);
                        pk[34] = __float_as_uint(s[1]); pk[35] = __float_as_uint(q[1]);
                    }
                    if (g == 6) {
#pragma unroll
                        for (int r = 0; r < 2; r++) { s[r] = __uint_as_float(pk[32 + 2 * r]); q[r] = __uint_as_float(pk[33 + 2 * r]); }
                        const bool hi = lane & 16, od = lane & 8;
                        float a = hi ? s[1] : s[0], b = hi ? q[1] : q[0];
                        a += __shfl_xor_sync(~0u, hi ? s[0] : s[1], 16);
                        b += __shfl_xor_sync(~0u, hi ? q[0] : q[1], 16);
                        float t = od ? b : a;
                        t += __shfl_xor_sync(~0u, od ? a : b, 8);
#pragma unroll
                        for (int o = 4; o; o >>= 1) t += __shfl_xor_sync(~0u, t, o);
#pragma unroll
                        for (int r = 0; r < 2; r++) {
                            s[r] = __shfl_sync(~0u, t, 16 * r);
                            q[r] = __shfl_sync(~0u, t, 16 * r + 8);
                        }
                        ln_finish(s[0], q[0], pk[36], pk[37], pk[38]);
                        ln_finish(s[1], q[1], pk[39], pk[40], pk[41]);
                    }
                    if (g == 7 + w) ln_apply<0>(pk, pk[36], pk[37], pk[38], ptr_off(g_xn, image_offset(ln_row, lane)));
                    if (g == 8) {
                        ln_apply<16>(pk, pk[39], pk[40], pk[41], ptr_off(g_xn, image_offset(ln_row + 1, lane)));
                        mark_done();
                    }
                }
            }
            wg_wait<0>();
            reg_fence(acc);
            release(g - 1);
            PROF(2 + 2 * item, w);
            if (w == 0) PROF_GT(2 + 2 * item);
            const int second = item == 1 || item == 4;
            if (w == 0) {
#pragma unroll
                for (int i = 0; i < 128; i++) acc[i] *= SM_SCALE;
            }
            reg_fence(acc);
#pragma unroll
            for (int i = 0; i < 64; i++) pk[i] = pack_bf16(acc[chunk_src(i)], acc[chunk_src(i) + 1]);
            pend = ptr_off(g_kv, ((pair & 15) * 16 + (pair >> 4) * 4 + second * 2) * 65536 + w * 32768 + c * 8192 + v * 2048 + chunk0);
            PROF(3 + 2 * item, w);
            continue;
        }

        float S[64];
        auto issue_q = [&](int first_acc) {
            wait_full(g);
            const uint32_t pg = sb + (g & 3) * (3 * PAGE);
            const uint64_t da = make_desc(pg + w * 8192, 16), db = make_desc(pg + 2 * PAGE, 8192);
            const uint64_t dab = make_desc(pg + PAGE + (1 - w) * 8192, 16);
            wg_fence();
#pragma unroll
            for (int q = 0; q < 4; q++) {
                wgmma_n128_ss(S, da + 2 * q, db + 128 * q, q ? 1 : first_acc);
                wgmma_n128_ss(O, dab + 2 * q, db + 128 * q, q ? 1 : first_acc);
            }
            wg_commit();
            g++;
        };
        auto issue_half = [&](float (&A)[64], uint32_t pg, uint32_t a_off) {
            const uint64_t da = make_desc(pg + a_off, 16), db = make_desc(pg + 2 * PAGE, 8192);
#pragma unroll
            for (int q = 0; q < 4; q++) wgmma_n128_ss(A, da + 2 * q, db + 128 * q, 1);
            wg_commit();
        };
        issue_q(0);
#pragma unroll 1
        for (int kb = 1; kb < DM / 64; kb++) {
            if (kb == DM / 64 - 3 && w == 1) bar_sync(4, 256);
            const bool defer = kb >= DM / 64 - 2;
            if (!defer) {
                issue_q(1);
            } else {
                wait_full(g);
                wg_fence();
                issue_half(S, sb + (g & 3) * (3 * PAGE), w * 8192);
                g++;
            }
            if (kb == DM / 64 - 2 && w == 0) bar_arrive(4, 256);
            wg_wait<1>();
            if (kb < DM / 64 - 1) release(g - 2);
            if (kb <= 8) {
                write_part(kb - 1);
                if (kb == 8) mark_done();
            }
        }
        uint32_t Q[32], Pm[32];
#pragma unroll
        for (int i = 0; i < 32; i++) Pm[i] = 0;
        float lim = (float)(v * 16 + (lane >> 2) - 8 * (lane & 3));
        l[0] = l[1] = 0.f;
        float mc[2] = {0.f, 0.f}, scale[2] = {0.f, 0.f}, sum[4];
        uint32_t kq = g * 8, vq = g * 8, ks = 0, vs = 0, ctl;
        int t = 0;
        reg_fence(Pm);
        asm volatile("" : "+f"(lim), "+f"(mc[0]), "+f"(mc[1]), "+f"(l[0]), "+f"(l[1]), "+f"(scale[0]), "+f"(scale[1]));
        asm volatile("" : "+r"(kq), "+r"(vq), "+r"(ks), "+r"(vs), "+r"(t));
        wg_wait<0>();
        reg_fence(S);
        reg_fence(O);
        PROF(2 + 2 * item, w);
        if (w == 0) PROF_GT(2 + 2 * item);

#pragma unroll
        for (int i = 0; i < 32; i++) Q[i] = pack_bf16(S[2 * i], S[2 * i + 1]);
        const uint32_t qpark = stg + lane * 16;
        constexpr int T = 17;
        uint32_t shifted = 0;
        uint32_t tick = 0;
        constexpr uint32_t SLOT = (2 * PAGE) >> 4;
        const uint32_t kdesc0 = (uint32_t)make_desc(sb, PAGE), vdesc0 = (uint32_t)make_desc(sb, 16);
        wait_full(g);
        do {
            bar_sync(2 + w, 256);
            wg_fence();
            issue_qk(S, Q, desc_hi | (kdesc0 + ks));
            wg_commit();
            ctl = __shfl_sync(~0u, ctl_tab, t);
            mbar_wait(sb + BAR_FULL + (vq & 56), (vq >> 6) & 1);
            uint32_t krel = empty_rel + (kq & 56), vrel = empty_rel + (vq & 56);
            const uint64_t vdesc = desc_hi | (vdesc0 + vs);
            if (ctl & (CTL_SWITCH | CTL_SKIPREL)) {
                if (ctl & CTL_SKIPREL) { release((kq >> 3) - 2); release((kq >> 3) + 1); }
                if (ctl & CTL_SWITCH) {
                    scale[0] = rcp_approx(quad_sum(l[0]));
                    scale[1] = rcp_approx(quad_sum(l[1]));
                    l[0] = l[1] = mc[0] = mc[1] = 0.f;
                    shifted = false;
                    pend = ptr_off(ctx_dst(item == 5, 0), chunk0);
                    asm volatile("" : "+l"(pend));
                }
            }
            const uint32_t kadv = (ctl >> 16) & 7, vadv = ctl >> 20;
            kq += kadv * 8; ks += kadv * SLOT; ks = ks >= 6 * SLOT ? ks - 6 * SLOT : ks;
            vq += vadv * 8; vs += vadv * SLOT; vs = vs >= 6 * SLOT ? vs - 6 * SLOT : vs;
            t++;
            uint32_t kbar = sb + BAR_FULL + (kq & 56), kpar = (kq >> 6) & 1;
            asm volatile("" : "+r"(krel), "+r"(vrel), "+r"(kbar), "+r"(kpar), "+r"(ks), "+r"(vs), "+r"(kq), "+r"(vq), "+r"(t));
            if (!(ctl & (CTL_START | CTL_PVHALF))) {
                wg_fence();
                issue_pv<0, 1>(O, Pm, vdesc, ctl & CTL_PVACC);
                wg_commit();
                issue_pv<1, 4>(O, Pm, vdesc, 1);
                wg_commit();
                issue_pv<4, 8>(O, Pm, vdesc, 1);
                wg_commit();
            } else if (ctl & CTL_PVHALF) {
                wg_fence();
                issue_pv<0, 1>(O, Pm, vdesc, ctl & CTL_PVACC);
                wg_commit();
                issue_pv<1, 4>(O, Pm, vdesc, 1);
                wg_commit();
                wg_commit();
            } else {
                wg_fence();
                issue_half(O, sb + 6 * PAGE, PAGE + (1 - w) * 8192);
                issue_half(O, sb + 9 * PAGE, PAGE + (1 - w) * 8192);
            }
            bar_arrive(3 - w, 256);
            auto scores_done = [&]() {
                sched_fence(tick, lane < 3);
                wg_wait<2>();
                reg_fence(S);
                if (lane < 3) mbar_arrive_cluster(krel);
            };
            auto load_q = [&]() {
#pragma unroll
                for (int i = 0; i < 8; i++) lds128(qpark + (i >> 2) * 8192 + (i & 3) * 512, Q[4 * i], Q[4 * i + 1], Q[4 * i + 2], Q[4 * i + 3]);
            };
            if ((ctl & (CTL_HALF | CTL_MASKHI | CTL_LOADQ)) || shifted) {
                scores_done();
                if (ctl & CTL_LOADQ) load_q();
                if (ctl & CTL_HALF) mask_half<0>(S, lim);
                if (ctl & CTL_MASKHI) mask_half<8>(S, lim);
                if (shifted) shift_rows(S, mc[0], mc[1]);
            } else {
                scores_done();
            }
            const bool kready = mbar_test(kbar, kpar);
            sum[0] = sum[1] = sum[2] = sum[3] = 0.f;
            float e[64];
#pragma unroll
            for (int i = 0; i < 16; i++) asm volatile("" : "+r"(Pm[i])::"memory");
            exp_stages<0, 16, 32, 4 + LAG>(S, e, Pm, sum, tick, lane < 3);
            auto pv_done = [&](bool rel) {
                sched_fence(tick, lane < 3);
                wg_wait<0>();
                reg_fence(O);
                if (rel && lane < 3) mbar_arrive_cluster(vrel);
#pragma unroll
                for (int i = 16; i < 32; i++) asm volatile("" : "+r"(Pm[i])::"memory");
            };
            const bool half = ctl & CTL_HALF, first = ctl & (CTL_START | CTL_SWITCH);
            float limit = SUM_HI;
            float a0 = 0.f, a1 = 0.f, ta = 0.f, tb = 0.f;
            auto low_check = [&](int k) {
                auto bfly = [](float x, int m) { float r; asm volatile("shfl.sync.bfly.b32 %0, %1, %2, 0x1f, 0xffffffff;" : "=f"(r) : "f"(x), "r"(m)); return r; };
                if (k == 16 + LAG) { a0 = sum[0] + sum[1]; a1 = sum[2] + sum[3]; asm volatile("" : "+f"(a0), "+f"(a1)); }
                if (k == 17 + LAG) { ta = bfly(a0, 1); tb = bfly(a1, 1); }
                if (k == 20 + LAG) { a0 += ta; a1 += tb; asm volatile("" : "+f"(a0), "+f"(a1)); }
                if (k == 21 + LAG) { ta = bfly(a0, 2); tb = bfly(a1, 2); }
                if (k == 24 + LAG) { if (!(fminf(a0 + ta, a1 + tb) >= SUM_LO)) limit = -1.f; asm volatile("" : "+f"(limit)); }
            };
            if (!(ctl & (CTL_HALF | CTL_SWITCH | CTL_START))) {
                pv_done(true);
                exp_stages<16, 32 + LAG, 32, -1>(S, e, Pm, sum, tick, lane < 3);
            } else if (half) {
                pv_done(!(ctl & CTL_START));
                exp_stages<16, 16 + LAG, 16, -1>(S, e, Pm, sum, tick, lane < 3);
                if (ctl & CTL_START) {
                    release(g - 2); release(g - 1);
#pragma unroll
                    for (int i = 0; i < 32; i++) Q[i] = pack_bf16(O[2 * i], O[2 * i + 1]);
                    if (!(fminf(quad_sum(sum[0] + sum[1]), quad_sum(sum[2] + sum[3])) >= SUM_LO)) limit = -1.f;
                }
            } else if (ctl & CTL_START) {
                pv_done(false);
                release(g - 2); release(g - 1);
                if (ctl & CTL_DIRECT) {
                    exp_stages<16, 32 + LAG, 32, -1>(S, e, Pm, sum, tick, lane < 3, [&](int k) {
                        low_check(k);
                        if (k < 32) {
#pragma unroll
                            for (int i = 2 * (k - 16); i < 2 * (k - 16) + 2; i++)
                                asm volatile("cvt.rn.bf16x2.f32 %0, %1, %2;" : "=r"(Q[i]) : "f"(O[2 * i + 1]), "f"(O[2 * i]));
                        }
                    });
                } else {
                    uint32_t u[32] = {};
                    exp_stages<16, 32 + LAG, 32, -1>(S, e, Pm, sum, tick, lane < 3, [&](int k) {
                        low_check(k);
                        if (k < 32) {
#pragma unroll
                            for (int i = 2 * (k - 16); i < 2 * (k - 16) + 2; i++)
                                asm volatile("cvt.rn.bf16x2.f32 %0, %1, %2;" : "=r"(u[i]) : "f"(O[2 * i + 1]), "f"(O[2 * i]));
                        }
                        const int i = (k - 18) >> 1;
                        if (k >= 18 && !(k & 1) && i < 8) sts128(qpark + (i >> 2) * 8192 + (i & 3) * 512, u[4 * i], u[4 * i + 1], u[4 * i + 2], u[4 * i + 3]);
                    });
                }
            } else {
                pv_done(true);
                uint8_t* d[2] = {pend, (uint8_t*)((uintptr_t)pend ^ 64)};
                uint32_t po[32] = {};
                exp_stages<16, 32 + LAG, 32, -1>(S, e, Pm, sum, tick, lane < 3, [&](int k) {
                    low_check(k);
                    const int q = (k - 18) >> 1;
                    if (k >= 19 && (k & 1) && q < 8)
                        st16cs(reinterpret_cast<uint4*>(d[(q >> 1) & 1] + (q >> 2) * PAGE + (q & 1) * 1024), make_uint4(po[4 * q], po[4 * q + 1], po[4 * q + 2], po[4 * q + 3]));
                    if (k >= 32) return;
                    const int i = (k - 16) >> 1, h = (k & 1) * 2;
                    const float sc = scale[i & 1];
#pragma unroll
                    for (int r = h; r < h + 2; r++) {
                        float x0, x1;
                        asm volatile("mul.f32 %0, %1, %2;" : "=f"(x0) : "f"(O[chunk_src(4 * i + r)]), "f"(sc));
                        asm volatile("mul.f32 %0, %1, %2;" : "=f"(x1) : "f"(O[chunk_src(4 * i + r) + 1]), "f"(sc));
                        asm volatile("cvt.rn.bf16x2.f32 %0, %1, %2;" : "=r"(po[4 * i + r]) : "f"(x1), "f"(x0));
                    }
                });
                mark_done();
            }
            sum[0] += sum[1]; sum[2] += sum[3];
            float chk = sum[0] + sum[2];
            const bool bad = !(chk <= limit);
            if (__any_sync(~0u, bad)) {
                if (half) {
#pragma unroll
                    for (int i = 32; i < 64; i++) S[i] = -INFINITY;
                }
                float d0 = fmaxf(S[0], S[1]), d1 = fmaxf(S[2], S[3]);
#pragma unroll
                for (int j = 1; j < 16; j++) {
                    d0 = fmaxf(d0, fmaxf(S[4 * j], S[4 * j + 1]));
                    d1 = fmaxf(d1, fmaxf(S[4 * j + 2], S[4 * j + 3]));
                }
                d0 = fmaxf(d0, __shfl_xor_sync(~0u, d0, 1));
                d1 = fmaxf(d1, __shfl_xor_sync(~0u, d1, 1));
                d0 = fmaxf(d0, __shfl_xor_sync(~0u, d0, 2));
                d1 = fmaxf(d1, __shfl_xor_sync(~0u, d1, 2));
                if (!first) {
                    d0 = fmaxf(d0, 0.f);
                    d1 = fmaxf(d1, 0.f);
                    const float a0 = ex2(-d0), a1 = ex2(-d1);
#pragma unroll
                    for (int j = 0; j < 16; j++) {
                        O[4 * j] *= a0; O[4 * j + 1] *= a0; O[4 * j + 2] *= a1; O[4 * j + 3] *= a1;
                    }
                    l[0] *= a0; l[1] *= a1;
                }
                mc[0] += d0; mc[1] += d1;
                shifted = true;
                shift_rows(S, d0, d1);
                sum[0] = sum[1] = sum[2] = sum[3] = 0.f;
                exp_part<0, 8>(S, Pm, sum);
                exp_part<8, 16>(S, Pm, sum);
                sum[0] += sum[1]; sum[2] += sum[3];
            }
            l[0] += sum[0]; l[1] += sum[2];
            if (!kready) mbar_wait(kbar, kpar);
        } while (t < T);
        asm volatile("" : "+r"(t));
        g += 36;
        if (t > T) asm volatile("st.shared.u32 [%0], %1;" ::"r"(sb + SM_PROF), "r"(tick) : "memory");
        const uint64_t vdesc = desc_hi | (vdesc0 + vs);
        wait_full(vq >> 3);
        if (ctl & CTL_HALF) {
            wg_fence();
            issue_pv<0, 4>(O, Pm, vdesc, !(ctl & CTL_SWITCH));
            wg_commit();
        } else {
            wg_fence();
            issue_pv<0, 4>(O, Pm, vdesc, !(ctl & CTL_SWITCH));
            issue_pv<4, 8>(O, Pm, vdesc, 1);
            wg_commit();
        }
        if (item == 5) break;
        finish_attention(0, g);
        PROF(3 + 2 * item, w);
        if (w == 0) PROF_GT(3 + 2 * item);
    }

    float acc[64];
    uint32_t slot = 0;
    const uint32_t da0 = (uint32_t)make_desc(sb + w * 8192, 16), db0 = (uint32_t)make_desc(sb + PAGE, 8192);
    uint32_t da = da0, db = db0, fbar = sb + BAR_FULL + (g & 7) * 8, fpar = (g >> 3) & 1, rel = 0;
    auto issue_out = [&](int first_acc) {
        mbar_wait(fbar, fpar);
        wg_fence();
#pragma unroll
        for (int q = 0; q < 4; q++) wgmma_n128_ss(acc, (desc_hi | da) + 2 * q, (desc_hi | db) + 128 * q, q ? 1 : first_acc);
        wg_commit();
        rel = empty_rel + ((g - 1) & 7) * 8;
        g++;
        slot = slot == SM_REGION - 2 * PAGE ? 0 : slot + 2 * PAGE;
        da = da0 + (slot >> 4); db = db0 + (slot >> 4);
        fbar = sb + BAR_FULL + (g & 7) * 8; fpar = (g >> 3) & 1;
        asm volatile("" : "+r"(da), "+r"(db), "+r"(fbar), "+r"(fpar), "+r"(rel), "+r"(slot), "+r"(g));
    };
    issue_out(0);
    finish_attention(1, g - 1);
    PROF(13, w);
    if (w == 0) PROF_GT(13);
    uint32_t xr[32], gr[32];
#pragma unroll
    for (int i = 0; i < 32; i++) gr[i] = 0;
#pragma unroll 1
    for (int kb = 1; kb < 64; kb++) {
        if (kb == 60 && w == 1) bar_sync(4, 256);
        issue_out(1);
        if (kb == 63 && w == 0) bar_arrive(4, 256);
        wg_wait<1>();
        if (kb < 60 && lane < 3) mbar_arrive_cluster(rel);
        if (kb <= 8 && !(kb & 1)) {
            store_part4(pend, (kb >> 1) - 1, pk);
            if (kb == 8) mark_done();
        }
        if (kb >= 28 && kb < 60 && (kb & 3) == 2 * w) {
            uint32_t u0, u1, u2, u3;
            const int s = (kb - 28) >> 2;
            mbar_wait(sb + BAR_G + w * 8, 0);
            ldmatrix_x4(slab_addr(stg, lane, s), u0, u1, u2, u3);
            set_quad(gr, s, pack_bf16(silu_f(bf_lo(u0)), silu_f(bf_hi(u0))), pack_bf16(silu_f(bf_lo(u1)), silu_f(bf_hi(u1))),
                     pack_bf16(silu_f(bf_lo(u2)), silu_f(bf_hi(u2))), pack_bf16(silu_f(bf_lo(u3)), silu_f(bf_hi(u3))));
        }
    }
    mbar_wait(fbar, fpar);
    const uint32_t xs = sb + slot + w * PAGE + v * 2048;
#pragma unroll
    for (int s = 0; s < 8; s++) ldmatrix_x4(slab_addr(xs, lane, s), xr[4 * s], xr[4 * s + 1], xr[4 * s + 2], xr[4 * s + 3]);
    wg_wait<0>();
    reg_fence(acc);
    PROF(14, w);
    if (w == 0) PROF_GT(14);
#pragma unroll
    for (int s = 0; s < 8; s++) {
        uint32_t o[4];
#pragma unroll
        for (int k = 0; k < 4; k++)
            o[k] = bf2_add(xr[4 * s + k], bf2_mul(pack_bf16(acc[8 * s + 2 * k], acc[8 * s + 2 * k + 1]), gr[4 * s + k]));
        stmatrix_x4(slab_addr(stg, lane, s), o[0], o[1], o[2], o[3]);
        if ((s & 3) == 3) {
            fence_async_smem();
            __syncwarp();
            const int orow = ((pair >> 1) & 7) * 256 + c * 128 + w * 64 + v * 16, ocol = (pair >> 4) * 256 + (pair & 1) * 128;
            if (lane == 0) tma_store_2d(m_out, ocol + (s >> 2) * 64, orow, stg + (s >> 2) * 8192);
        }
    }
    PROF(28, w);
    if (lane == 0) {
        bulk_commit();
        bulk_wait_read();
    }
    __syncwarp();
}

__global__ void __cluster_dims__(2, 1, 1) __launch_bounds__(384, 1)
fused_kernel(const __grid_constant__ CUtensorMap m_ckv, const __grid_constant__ CUtensorMap m_wuk,
             const __grid_constant__ CUtensorMap m_wuv, const __grid_constant__ CUtensorMap m_wq,
             const __grid_constant__ CUtensorMap m_wo, const __grid_constant__ CUtensorMap m_x,
             const __grid_constant__ CUtensorMap m_out, const __grid_constant__ CUtensorMap m_gate,
             const __grid_constant__ CUtensorMap m_up, const __grid_constant__ CUtensorMap m_down, const Params P) {
    extern __shared__ __align__(1024) uint8_t smem[];
    const uint32_t sb = __shfl_sync(~0u, smem_u32(smem), 0);
    const int tid = threadIdx.x;
    const int cl = blockIdx.x >> 1, c = blockIdx.x & 1;
    const int pair = cl >= 64 ? cl : cl < 4 ? cl * 16 + 15 : cl < 36 ? ((cl - 4) >> 3) * 16 + ((cl - 4) & 7)
                                                                    : ((cl - 36) / 7) * 16 + 8 + (cl - 36) % 7;
    const int warp = __shfl_sync(~0u, tid >> 5, 0), lane = tid & 31;
    auto init_barriers = [&](int i0, int i1) {
#pragma unroll
        for (int i = i0; i < i1; i++) mbar_init(sb + SM_BAR + i * 8, (i >> 3) == 1 ? 16 : i >= 25 ? 8 : 1);
        asm volatile("fence.mbarrier_init.release.cluster;" ::: "memory");
    };
    auto finish = [&]() {
        PROF(29, tid >> 7);
        if (tid == 0) atomicAdd(&g_sync.done, 1u);
    };
    if (pair >= NMAIN / 2) {
        if (tid == 256) init_barriers(0, 16);
        if (tid == 288) *reinterpret_cast<uint32_t*>(smem + PAUSE) = 0;
        __syncthreads();
        const unsigned epoch = __ldcg(&g_sync.done) / NCTA;
        if (warp < 8) ffn_cta(smem, sb, blockIdx.x - NMAIN, epoch, P.w_r);
        else if (tid == 256) ffn_producer(sb, blockIdx.x - NMAIN, epoch + 1, &m_gate, &m_up, &m_down);
        else if (tid == 288) ffn_pacer(sb, epoch + 1);
        __syncwarp();
        finish();
    } else if (warp < 8) {
        const uint32_t r0 = tid >> 3, ch = tid & 7, dst = sb + r0 * 128 + ((ch ^ (r0 & 7)) << 4);
        const uint32_t wo = r0 * 8192 + (pair & 15) * 256 + c * 128 + ch * 16;
        const uint8_t* sw[2] = {ptr_off(P.w_uk, wo), ptr_off(P.w_uv, wo)};
        const uint8_t* sc = ptr_off(P.c_kv, ((pair >> 4) * 512 + r0) * 1024 + ch * 16);
#pragma unroll
        for (int i = 0; i < 4; i++) cp_async16(dst + i * 4096, sw[i >> 1] + (i & 1) * 262144);
#pragma unroll
        for (int i = 0; i < 8; i++) cp_async16(dst + PAGE + i * 4096, sc + i * 32768);
        asm volatile("barrier.cluster.arrive.relaxed.aligned;" ::: "memory");
        asm volatile("setmaxnreg.inc.sync.aligned.u32 240;");
        consumer(sb, pair, c, &m_out, (const uint8_t*)P.x);
        finish();
    } else {
        asm volatile("setmaxnreg.dec.sync.aligned.u32 24;");
        auto load_w = [&](int kb) {
            tma_3d(sb + kb * (3 * PAGE), &m_wuk, 0, kb * 64, (pair & 15) * 2 + c, sb + BAR_FULL + kb * 8);
            tma_3d(sb + kb * (3 * PAGE) + 8192, &m_wuv, 0, kb * 64, (pair & 15) * 2 + c, sb + BAR_FULL + kb * 8);
        };
        if (tid == 256) {
            init_barriers(0, NBAR);
            prefetch_map(&m_ckv);
            prefetch_map(&m_wuv);
            mbar_arrive(sb + BAR_FULL);
#pragma unroll 1
            for (int kb = 1; kb < 4; kb++) {
                mbar_expect_tx(sb + BAR_FULL + kb * 8, 3 * PAGE);
                if (kb <= 1) load_w(kb);
            }
        }
        PROF(18, 0);
        __syncwarp();
        cluster_sync();
        PROF(22, 0);
        if (tid == 256) {
#pragma unroll 1
            for (int kb = 1; kb < 4; kb++) {
                if (kb > 1) load_w(kb);
                tma_3d_mc(sb + kb * (3 * PAGE) + (1 + c) * PAGE, &m_ckv, 0, (pair >> 4) * 512 + c * 128, kb, sb + BAR_FULL + kb * 8);
            }
        }
        __syncwarp();
        PROF(19, 0);
        if (warp == 10) {
            sync_helper(sb, lane, pair, c);
        } else if (warp & 1) {
            fetch_helper(P.c_kv, sb, (warp >> 1) & 1, lane, pair, c);
        } else {
            producer(P, sb, pair, c, &m_ckv, &m_wuk, &m_wuv, &m_wq, &m_wo, &m_x, &m_out);
        }
    }
}

typedef CUresult (*EncodeFn)(CUtensorMap*, CUtensorMapDataType, cuuint32_t, void*, const cuuint64_t*, const cuuint64_t*,
                             const cuuint32_t*, const cuuint32_t*, CUtensorMapInterleave, CUtensorMapSwizzle,
                             CUtensorMapL2promotion, CUtensorMapFloatOOBfill);

void make_map_2d(EncodeFn fn, CUtensorMap* m, const void* ptr, int rows, int cols, int box_rows) {
    cuuint64_t dims[2] = {(cuuint64_t)cols, (cuuint64_t)rows};
    cuuint64_t strides[1] = {(cuuint64_t)cols * 2};
    cuuint32_t box[2] = {64, (cuuint32_t)box_rows};
    cuuint32_t es[2] = {1, 1};
    fn(m, CU_TENSOR_MAP_DATA_TYPE_BFLOAT16, 2, const_cast<void*>(ptr), dims, strides, box, es, CU_TENSOR_MAP_INTERLEAVE_NONE,
       CU_TENSOR_MAP_SWIZZLE_128B, CU_TENSOR_MAP_L2_PROMOTION_L2_256B, CU_TENSOR_MAP_FLOAT_OOB_FILL_NONE);
}
void make_map_w(EncodeFn fn, CUtensorMap* m, const void* ptr, int rows, int cols, int blocks, int box_rows) {
    cuuint64_t dims[3] = {64, (cuuint64_t)rows, (cuuint64_t)cols / 64};
    cuuint64_t strides[2] = {(cuuint64_t)cols * 2, 128};
    cuuint32_t box[3] = {64, (cuuint32_t)box_rows, (cuuint32_t)blocks};
    cuuint32_t es[3] = {1, 1, 1};
    fn(m, CU_TENSOR_MAP_DATA_TYPE_BFLOAT16, 3, const_cast<void*>(ptr), dims, strides, box, es, CU_TENSOR_MAP_INTERLEAVE_NONE,
       CU_TENSOR_MAP_SWIZZLE_128B, CU_TENSOR_MAP_L2_PROMOTION_L2_128B, CU_TENSOR_MAP_FLOAT_OOB_FILL_NONE);
}

void make_map_wo(EncodeFn fn, CUtensorMap* m, const void* ptr) {
    cuuint64_t dims[5] = {DM, 2, 4, 4, NH * 128 / 32};
    cuuint64_t strides[4] = {DM * 2, 8 * DM * 2, 2 * DM * 2, 32 * DM * 2};
    cuuint32_t box[5] = {64, 2, 4, 4, 2};
    cuuint32_t es[5] = {1, 1, 1, 1, 1};
    fn(m, CU_TENSOR_MAP_DATA_TYPE_BFLOAT16, 5, const_cast<void*>(ptr), dims, strides, box, es, CU_TENSOR_MAP_INTERLEAVE_NONE,
       CU_TENSOR_MAP_SWIZZLE_128B, CU_TENSOR_MAP_L2_PROMOTION_L2_256B, CU_TENSOR_MAP_FLOAT_OOB_FILL_NONE);
}

}

extern "C" void kernel_launch(void* const* d_in, const int* in_sizes, int n_in, void* d_out, int out_size) {
    static EncodeFn fn = nullptr;
    if (!fn) {
        void* f = nullptr;
        cudaDriverEntryPointQueryResult qr;
        cudaGetDriverEntryPoint("cuTensorMapEncodeTiled", &f, cudaEnableDefault, &qr);
        fn = (EncodeFn)f;
        cudaFuncSetAttribute(fused_kernel, cudaFuncAttributeMaxDynamicSharedMemorySize, SMEM_BYTES);
    }
    CUtensorMap m_ckv, m_wuk, m_wuv, m_wq, m_wo, m_x, m_out, m_gate, m_up, m_down;
    make_map_w(fn, &m_gate, d_in[8], DM, FF, FS / 64, 16);
    make_map_w(fn, &m_up, d_in[9], DM, FF, FS / 64, 16);
    make_map_w(fn, &m_down, d_in[10], FF, DM, DM / 64, 16);
    make_map_w(fn, &m_ckv, d_in[1], SEQ, DC, 1, 128);
    make_map_w(fn, &m_wq, d_in[2], DM, NH * 128, 1, 64);
    make_map_w(fn, &m_wuk, d_in[3], DC, NH * 128, 1, 64);
    make_map_w(fn, &m_wuv, d_in[4], DC, NH * 128, 1, 64);
    make_map_wo(fn, &m_wo, d_in[5]);
    make_map_w(fn, &m_x, d_in[0], SEQ, DM, 2, 64);
    make_map_2d(fn, &m_out, d_out, SEQ, DM, 16);
    Params P;
    P.x = (const __nv_bfloat16*)d_in[0];
    P.w_r = (const __nv_bfloat16*)d_in[7];
    P.c_kv = (const uint8_t*)d_in[1];
    P.w_uk = (const uint8_t*)d_in[3];
    P.w_uv = (const uint8_t*)d_in[4];
    P.w_o = (const uint8_t*)d_in[5];
    fused_kernel<<<NCTA, 384, SMEM_BYTES>>>(m_ckv, m_wuk, m_wuv, m_wq, m_wo, m_x, m_out, m_gate, m_up, m_down, P);
}
```
